```python
import torch

def _softmax(x, axis=-1):
    return torch.softmax(x, dim=axis)

def _gelu(x):
    return torch.nn.functional.gelu(x, approximate='tanh')

def _silu(x):
    return torch.nn.functional.silu(x)

def _sigmoid(x):
    return torch.sigmoid(x)

def _layernorm(x, axis=-1, eps=1e-05):
    m = x.mean(dim=axis, keepdim=True)
    v = x.var(dim=axis, keepdim=True, unbiased=False)
    return (x - m) / torch.sqrt(v + eps)

def _scatter_add(tgt, idx, src, axis=0):
    return tgt.clone().index_add_(axis, idx, src)

def _segment_sum(src, seg, n):
    out = torch.zeros((n,) + src.shape[1:], dtype=src.dtype)
    return out.index_add_(0, seg, src)

def _pad(x, pw):
    flat = tuple((v for pair in reversed(pw) for v in pair))
    return torch.nn.functional.pad(x, flat)
kernel_name = 'adaLN_cond__gqa_block_cached__swiglu_ffn__decode'

def setup_inputs():

    _w = lambda a: (lambda t: t.to(torch.bfloat16) if t.is_floating_point() else t)(torch.as_tensor(a))

    def _A_setup():
        B, Sq, D = (1, 1, 576)
        Hq, Hkv, Sk, Dh = (32, 16, 65536, 128)
        assert Hq % Hkv == 0, (Hq, Hkv)
        return {'x': _w((lambda *s: torch.randn(*s, dtype=torch.bfloat16) * 0.05)(B, Sq, D)), 'k_cache': _w((lambda *s: torch.randn(*s, dtype=torch.bfloat16) * 3.2)(B, Hkv, Sk, Dh)), 'v_cache': _w((lambda *s: torch.randn(*s, dtype=torch.bfloat16) * 0.4)(B, Hkv, Sk, Dh)), 'wq': _w((lambda *s: torch.randn(*s, dtype=torch.bfloat16) * 3.2)(D, Hq * Dh) * D ** (-0.5)), 'wo': _w((lambda *s: torch.randn(*s, dtype=torch.bfloat16) * 0.4)(Hq * Dh, D) * (Hq * Dh) ** (-0.5))}
    _A_in = _A_setup()

    def _B_setup():
        B, S, D, F = (1, 1, 576, 4608)
        return {'x': _w((lambda *s: torch.randn(*s, dtype=torch.bfloat16) * 0.05)(B, S, D)), 'w_gate': _w((lambda *s: torch.randn(*s, dtype=torch.bfloat16) * 0.05)(D, F)), 'w_up': _w((lambda *s: torch.randn(*s, dtype=torch.bfloat16) * 0.05)(D, F)), 'w_down': _w((lambda *s: torch.randn(*s, dtype=torch.bfloat16) * 0.05)(F, D))}
    _B_in = _B_setup()
    return {'A_x': _A_in['x'], 'A_k_cache': _A_in['k_cache'], 'A_v_cache': _A_in['v_cache'], 'A_wq': _A_in['wq'], 'A_wo': _A_in['wo'], 'B_x': _B_in['x'], 'B_w_gate': _B_in['w_gate'], 'B_w_up': _B_in['w_up'], 'B_w_down': _B_in['w_down'], 'c': _w((lambda *s: torch.randn(*s, dtype=torch.bfloat16) * 0.2)(1, 576) * 8.0), 'w_mod': _w((lambda *s: torch.randn(*s, dtype=torch.bfloat16) * 0.2)(576, 6 * 576) * 576 ** (-0.5) * 8.0)}

def reference(A_x, A_k_cache, A_v_cache, A_wq, A_wo, B_x, B_w_gate, B_w_up, B_w_down, c, w_mod):

    def _A_ref(x, k_cache, v_cache, wq, wo):
        B, Sq, D = x.shape
        Hq, Dh = (32, 128)
        Hkv = k_cache.shape[1]
        rep = Hq // Hkv
        q = (lambda x, *d: x.permute(*d))((x @ wq).reshape(B, Sq, Hq, Dh), 0, 2, 1, 3)
        k = (lambda x, n, axis: torch.repeat_interleave(x, n, dim=axis))(k_cache, rep, axis=1)
        v = (lambda x, n, axis: torch.repeat_interleave(x, n, dim=axis))(v_cache, rep, axis=1)
        scores = torch.einsum('bhqd,bhkd->bhqk', q, k) * Dh ** (-0.5)
        p = _softmax(scores, axis=-1)
        o = torch.einsum('bhqk,bhkd->bhqd', p, v)
        return (lambda x, *d: x.permute(*d))(o, 0, 2, 1, 3).reshape(B, Sq, Hq * Dh) @ wo

    def _B_ref(x, w_gate, w_up, w_down):
        g = _silu(x @ w_gate)
        u = x @ w_up
        return g * u @ w_down
    x = A_x
    mod = (_silu(c) @ w_mod).reshape(c.shape[0], 6, 1, -1)
    sa, ca, ga, sb, cb, gb = (mod[:, 0].clone(), mod[:, 1].clone(), mod[:, 2].clone(), mod[:, 3].clone(), mod[:, 4].clone(), mod[:, 5].clone())
    h = _layernorm(x, axis=-1) * (1 + ca) + sa
    x = x + ga * _A_ref(h, A_k_cache, A_v_cache, A_wq, A_wo)
    h = _layernorm(x, axis=-1) * (1 + cb) + sb
    x = x + gb * _B_ref(h, B_w_gate, B_w_up, B_w_down)
    return x
```

```cpp
#include <cuda_runtime.h>
#include <cuda_bf16.h>
#include <cuda.h>
#include <stdint.h>

namespace {

constexpr int D = 576, HKV = 16, SK = 65536, DH = 128, FF = 4608, NMOD = 6 * D, NQ = 4096;
constexpr int R = 32;
constexpr int TPH = SK / R;
constexpr int TPH_SHIFT = 11;
constexpr int NT = HKV * TPH;
constexpr int S = 5;
constexpr int STAGE_BYTES = 2 * R * DH * 2;
constexpr int MAXG = 144;
constexpr int NJOB = 128;
constexpr int NMODA = 2 * D / 16;
constexpr int NMODB = 4 * D / 16;
constexpr int NRED = D / 8;
constexpr int ROWP = 1168;

constexpr int OFF_RING = 0;
constexpr int OFF_W1 = OFF_RING + S * STAGE_BYTES;
constexpr int W1_BYTES = 2 * 576 * 80;
constexpr int OFF_W2 = OFF_W1 + W1_BYTES;
constexpr int W2_BYTES = 32 * ROWP;
constexpr int OFF_QS = OFF_W2 + W2_BYTES;
constexpr int OFF_MB = OFF_QS + NQ * 2;
constexpr int MB_FLOATS = 4 * 2 * 132;
constexpr int OFF_XS = OFF_MB + 2 * MB_FLOATS * 4;
constexpr int OFF_VEC = OFF_XS + D * 2;
constexpr int OFF_RED = OFF_VEC + D * 2;
constexpr int OFF_SM = OFF_RED + 384 * 4;
constexpr int OFF_BAR = OFF_SM + 128;
constexpr int SMEM_BYTES = OFF_BAR + 256;
static_assert(SMEM_BYTES <= 232448, "smem");
static_assert(40 * ROWP <= S * STAGE_BYTES, "down fits ring");

constexpr float SCALE_LOG2 = 0.08838834764831845f * 1.4426950408889634f;
constexpr unsigned SPIN_LIMIT = 1u << 22;

__device__ unsigned g_epoch;
__device__ unsigned g_ticket;
__device__ unsigned g_ydone;
__device__ __align__(16) uint32_t g_mod[NMOD];
__device__ __align__(16) unsigned long long g_q[NQ / 2];
__device__ __align__(16) float g_recO[HKV * 8 * MAXG * 32];
__device__ __align__(16) float g_recML[HKV * 2 * MAXG * 2];
__device__ __align__(16) float g_yacc[D];
__device__ __align__(16) float g_y15[8 * D];
__device__ __align__(16) float g_z[NJOB * D];

__device__ __forceinline__ uint32_t smem_u32(const void* p) { return (uint32_t)__cvta_generic_to_shared(p); }
__device__ __forceinline__ void mbar_init(uint32_t bar, uint32_t cnt) {
  asm volatile("mbarrier.init.shared::cta.b64 [%0], %1;" ::"r"(bar), "r"(cnt) : "memory");
}
__device__ __forceinline__ void mbar_expect_tx(uint32_t bar, uint32_t bytes) {
  asm volatile("mbarrier.arrive.expect_tx.shared::cta.b64 _, [%0], %1;" ::"r"(bar), "r"(bytes) : "memory");
}
__device__ __forceinline__ void mbar_arrive(uint32_t bar) {
  asm volatile("mbarrier.arrive.shared::cta.b64 _, [%0];" ::"r"(bar) : "memory");
}
__device__ __forceinline__ bool mbar_try(uint32_t bar, uint32_t parity) {
  uint32_t ok;
  asm volatile("{\n.reg .pred p;\nmbarrier.try_wait.parity.shared::cta.b64 p, [%1], %2;\nselp.u32 %0, 1, 0, p;\n}"
               : "=r"(ok) : "r"(bar), "r"(parity) : "memory");
  return ok != 0;
}
__device__ __forceinline__ void mbar_wait(uint32_t bar, uint32_t parity) {
  unsigned n = 0;
  while (!mbar_try(bar, parity)) {
    if (++n > SPIN_LIMIT) __trap();
  }
}
__device__ __forceinline__ void bulk_load(uint32_t dst, const void* src, uint32_t bytes, uint32_t bar) {
  asm volatile("cp.async.bulk.shared::cluster.global.mbarrier::complete_tx::bytes [%0], [%1], %2, [%3];"
               ::"r"(dst), "l"(src), "r"(bytes), "r"(bar) : "memory");
}
__device__ __forceinline__ void tma2d(uint32_t dst, const CUtensorMap* m, int c0, int c1, uint32_t bar) {
  asm volatile("cp.async.bulk.tensor.2d.shared::cluster.global.mbarrier::complete_tx::bytes [%0], [%1, {%3,%4}], [%2];"
               ::"r"(dst), "l"(m), "r"(bar), "r"(c0), "r"(c1) : "memory");
}
__device__ __forceinline__ void tma3d(uint32_t dst, const CUtensorMap* m, int c0, int c1, int c2, uint32_t bar) {
  asm volatile("cp.async.bulk.tensor.3d.shared::cluster.global.mbarrier::complete_tx::bytes [%0], [%1, {%3,%4,%5}], [%2];"
               ::"r"(dst), "l"(m), "r"(bar), "r"(c0), "r"(c1), "r"(c2) : "memory");
}
__device__ __forceinline__ void prefetch_map(const CUtensorMap* m) {
  asm volatile("prefetch.tensormap [%0];" ::"l"(m) : "memory");
}
__device__ __forceinline__ void named_sync(int id, int n) { asm volatile("bar.sync %0, %1;" ::"r"(id), "r"(n) : "memory"); }
__device__ __forceinline__ void ldsm4(uint32_t a, uint32_t& r0, uint32_t& r1, uint32_t& r2, uint32_t& r3) {
  asm volatile("ldmatrix.sync.aligned.m8n8.x4.shared.b16 {%0,%1,%2,%3}, [%4];"
               : "=r"(r0), "=r"(r1), "=r"(r2), "=r"(r3) : "r"(a) : "memory");
}
__device__ __forceinline__ void ldsm4t(uint32_t a, uint32_t& r0, uint32_t& r1, uint32_t& r2, uint32_t& r3) {
  asm volatile("ldmatrix.sync.aligned.m8n8.x4.trans.shared.b16 {%0,%1,%2,%3}, [%4];"
               : "=r"(r0), "=r"(r1), "=r"(r2), "=r"(r3) : "r"(a) : "memory");
}
__device__ __forceinline__ void ldsm2t(uint32_t a, uint32_t& r0, uint32_t& r1) {
  asm volatile("ldmatrix.sync.aligned.m8n8.x2.trans.shared.b16 {%0,%1}, [%2];"
               : "=r"(r0), "=r"(r1) : "r"(a) : "memory");
}
__device__ __forceinline__ void ldsm1t(uint32_t a, uint32_t& r0) {
  asm volatile("ldmatrix.sync.aligned.m8n8.x1.trans.shared.b16 {%0}, [%1];" : "=r"(r0) : "r"(a) : "memory");
}
__device__ __forceinline__ void mma16816(float (&c)[4], uint32_t a0, uint32_t a1, uint32_t a2, uint32_t a3,
                                         uint32_t b0, uint32_t b1) {
  asm volatile("mma.sync.aligned.m16n8k16.row.col.f32.bf16.bf16.f32 {%0,%1,%2,%3}, {%4,%5,%6,%7}, {%8,%9}, {%0,%1,%2,%3};"
               : "+f"(c[0]), "+f"(c[1]), "+f"(c[2]), "+f"(c[3])
               : "r"(a0), "r"(a1), "r"(a2), "r"(a3), "r"(b0), "r"(b1));
}
__device__ __forceinline__ void mma1688(float (&c)[4], uint32_t a0, uint32_t a1, uint32_t b0) {
  asm volatile("mma.sync.aligned.m16n8k8.row.col.f32.bf16.bf16.f32 {%0,%1,%2,%3}, {%4,%5}, {%6}, {%0,%1,%2,%3};"
               : "+f"(c[0]), "+f"(c[1]), "+f"(c[2]), "+f"(c[3])
               : "r"(a0), "r"(a1), "r"(b0));
}
__device__ __forceinline__ float bfr(float x) { return __bfloat162float(__float2bfloat16_rn(x)); }
__device__ __forceinline__ uint32_t pack_bf2(float lo, float hi) {
  uint32_t r;
  asm("cvt.rn.bf16x2.f32 %0, %1, %2;" : "=r"(r) : "f"(hi), "f"(lo));
  return r;
}
__device__ __forceinline__ float ex2(float x) {
  float r;
  asm("ex2.approx.ftz.f32 %0, %1;" : "=f"(r) : "f"(x));
  return r;
}
__device__ __forceinline__ void st_ll(unsigned long long* p, uint32_t v, uint32_t tag) {
  unsigned long long w = ((unsigned long long)tag << 32) | v;
  asm volatile("st.relaxed.gpu.global.b64 [%0], %1;" ::"l"(p), "l"(w) : "memory");
}
__device__ __forceinline__ uint32_t ld_relaxed32(const void* p) {
  uint32_t w;
  asm volatile("ld.relaxed.gpu.global.b32 %0, [%1];" : "=r"(w) : "l"(p) : "memory");
  return w;
}
__device__ __forceinline__ uint2 ld_relaxed64v(const void* p) {
  uint2 w;
  asm volatile("ld.relaxed.gpu.global.v2.b32 {%0,%1}, [%2];" : "=r"(w.x), "=r"(w.y) : "l"(p) : "memory");
  return w;
}
__device__ __forceinline__ uint4 ld_relaxed128(const void* p) {
  uint4 w;
  asm volatile("ld.relaxed.gpu.global.v4.b32 {%0,%1,%2,%3}, [%4];"
               : "=r"(w.x), "=r"(w.y), "=r"(w.z), "=r"(w.w) : "l"(p) : "memory");
  return w;
}
__device__ __forceinline__ void st_relaxed32(void* p, uint32_t v) {
  asm volatile("st.relaxed.gpu.global.b32 [%0], %1;" ::"l"(p), "r"(v) : "memory");
}
__device__ __forceinline__ void st_relaxed64v(void* p, uint32_t a, uint32_t b) {
  asm volatile("st.relaxed.gpu.global.v2.b32 [%0], {%1,%2};" ::"l"(p), "r"(a), "r"(b) : "memory");
}
__device__ __forceinline__ uint32_t tag2(float v, uint32_t tag) { return (__float_as_uint(v) & ~3u) | (tag & 3u); }
__device__ __forceinline__ bool ok2(uint32_t w, uint32_t tag) { return ((w ^ tag) & 3u) == 0u; }
__device__ __forceinline__ bool ok2(const uint4& w, uint32_t tag) {
  return (((w.x ^ tag) | (w.y ^ tag) | (w.z ^ tag) | (w.w ^ tag)) & 3u) == 0u;
}
__device__ __forceinline__ bool ok16(uint32_t w, uint32_t tag) { return ((w ^ tag) & 0xffffu) == 0u; }
__device__ __forceinline__ bool ok16(const uint4& w, uint32_t tag) {
  return (((w.x ^ tag) | (w.y ^ tag) | (w.z ^ tag) | (w.w ^ tag)) & 0xffffu) == 0u;
}
__device__ __forceinline__ float hi16(uint32_t w) { return __uint_as_float(w & 0xffff0000u); }
__device__ __forceinline__ void spin_check(unsigned& n) {
  if (++n > SPIN_LIMIT) __trap();
}
__device__ __forceinline__ uint4 ldg_nc128(const void* p) {
  uint4 w;
  asm volatile("ld.global.nc.L1::no_allocate.v4.b32 {%0,%1,%2,%3}, [%4];"
               : "=r"(w.x), "=r"(w.y), "=r"(w.z), "=r"(w.w) : "l"(p));
  return w;
}
__device__ __forceinline__ unsigned ld_acquire(const unsigned* p) {
  unsigned v;
  asm volatile("ld.acquire.gpu.global.u32 %0, [%1];" : "=r"(v) : "l"(p) : "memory");
  return v;
}
__device__ __forceinline__ void wait_counter(const unsigned* p, unsigned target) {
  unsigned n = 0;
  while (ld_acquire(p) != target) {
    __nanosleep(64);
    if (++n > SPIN_LIMIT) __trap();
  }
}
__device__ __forceinline__ void red_add_release(unsigned* p, unsigned v) {
  asm volatile("red.release.gpu.global.add.u32 [%0], %1;" ::"l"(p), "r"(v) : "memory");
}
__device__ __forceinline__ void red_add2(float* p, float a, float b) {
  asm volatile("red.relaxed.gpu.global.add.v2.f32 [%0], {%1,%2};" ::"l"(p), "f"(a), "f"(b) : "memory");
}
#define DBG_T(i) do { } while (0)

__device__ __forceinline__ float block_sum256(float v, float* red, int tid) {
#pragma unroll
  for (int o = 16; o > 0; o >>= 1) v += __shfl_xor_sync(0xffffffffu, v, o);
  if ((tid & 31) == 0) red[tid >> 5] = v;
  named_sync(1, 256);
  float s = 0.f;
#pragma unroll
  for (int i = 0; i < 8; i++) s += red[i];
  return s;
}

template <int NT>
struct Mod16 {
  static constexpr int RP = NT / 2;
  static constexpr int NP = (D + RP - 1) / RP;
  uint4 w[NP];
  float cv[NP];
  __device__ __forceinline__ void load(const __nv_bfloat16* wmod, const __nv_bfloat16* c, int col0, int t) {
#pragma unroll
    for (int i = 0; i < NP; i++) {
      const int row = (t >> 1) + RP * i;
      w[i] = make_uint4(0u, 0u, 0u, 0u);
      cv[i] = 0.f;
      if (row < D) {
        w[i] = ldg_nc128(wmod + (size_t)row * NMOD + col0 + (t & 1) * 8);
        cv[i] = __bfloat162float(c[row]);
      }
    }
  }
  __device__ __forceinline__ void finish(int col0, int t, float* red, uint32_t tag, int barid) {
    float acc[8];
#pragma unroll
    for (int j = 0; j < 8; j++) acc[j] = 0.f;
#pragma unroll
    for (int i = 0; i < NP; i++) {
      const float s = bfr(cv[i] / (1.f + __expf(-cv[i])));
      const uint32_t ww[4] = {w[i].x, w[i].y, w[i].z, w[i].w};
#pragma unroll
      for (int j = 0; j < 4; j++) {
        acc[2 * j] += s * __uint_as_float(ww[j] << 16);
        acc[2 * j + 1] += s * __uint_as_float(ww[j] & 0xffff0000u);
      }
    }
#pragma unroll
    for (int o = 2; o <= 16; o <<= 1)
#pragma unroll
      for (int j = 0; j < 8; j++) acc[j] += __shfl_xor_sync(0xffffffffu, acc[j], o);
    if ((t & 31) < 2) {
#pragma unroll
      for (int j = 0; j < 8; j++) red[(t >> 5) * 16 + (t & 1) * 8 + j] = acc[j];
    }
    named_sync(barid, NT);
    if (t < 16) {
      float r = 0.f;
#pragma unroll
      for (int wv = 0; wv < NT / 32; wv++) r += red[wv * 16 + t];
      st_relaxed32(&g_mod[col0 + t], (__float_as_uint(bfr(r)) & 0xffff0000u) | (tag & 0xffffu));
    }
  }
};

__device__ __forceinline__ float gemv32(uint32_t wbase, const __nv_bfloat16* vec, float* red, int tid) {
  const int warp = tid >> 5, lane = tid & 31, g = lane >> 2, t = lane & 3;
  const int np = warp & 1, kg = warp >> 1;
  const int mi = lane >> 3;
  float c0[4] = {0.f, 0.f, 0.f, 0.f}, c1[4] = {0.f, 0.f, 0.f, 0.f};
  const uint32_t* v32 = reinterpret_cast<const uint32_t*>(vec);
#pragma unroll
  for (int ks = 0; ks < 9; ks++) {
    const int k0 = (kg * 9 + ks) * 16;
    const int row = k0 + (mi & 1) * 8 + (lane & 7);
    const int chunk = 2 * np + (mi >> 1);
    uint32_t r0, r1, r2, r3;
    ldsm4t(wbase + row * 64 + ((chunk ^ ((row >> 1) & 3)) << 4), r0, r1, r2, r3);
    uint32_t a0 = (g == 0) ? v32[(k0 >> 1) + t] : 0u;
    uint32_t a2 = (g == 0) ? v32[(k0 >> 1) + 4 + t] : 0u;
    mma16816(c0, a0, 0u, a2, 0u, r0, r1);
    mma16816(c1, a0, 0u, a2, 0u, r2, r3);
  }
  if (g == 0) {
    float* rp = red + kg * 32 + np * 16 + 2 * t;
    rp[0] = c0[0]; rp[1] = c0[1]; rp[8] = c1[0]; rp[9] = c1[1];
  }
  named_sync(1, 256);
  float r = 0.f;
  if (tid < 32) r = red[tid] + red[32 + tid] + red[64 + tid] + red[96 + tid];
  return r;
}

struct Params {
  const __nv_bfloat16* x;
  const __nv_bfloat16* c;
  const __nv_bfloat16* wmod;
  const __nv_bfloat16* wo;
  const __nv_bfloat16* wdown;
  __nv_bfloat16* out;
};

enum { B_FULL = 0, B_EMPTY = S, B_WQ = 2 * S, B_Q0, B_QALL, B_WO, B_GATE, B_UP, B_DOWN, B_W1FREE, B_MFULL0, B_MFULL1,
       B_MFREE0, B_MFREE1, B_COUNT };
static_assert(B_COUNT * 8 <= 192, "barrier area");

__global__ void __launch_bounds__(288, 1)
fused_kernel(const __grid_constant__ CUtensorMap mapK, const __grid_constant__ CUtensorMap mapV,
             const __grid_constant__ CUtensorMap mapWq, const __grid_constant__ CUtensorMap mapGate,
             const __grid_constant__ CUtensorMap mapUp, const Params p) {
  extern __shared__ __align__(1024) unsigned char sp[];
  const uint32_t sb = smem_u32(sp);
  if (sb & 1023u) __trap();
  const int tid = threadIdx.x, warp = tid >> 5, lane = tid & 31;
  const int cta = blockIdx.x, G = gridDim.x;
  const uint32_t bar0 = sb + OFF_BAR;
  auto BAR = [&](int i) { return bar0 + 8u * i; };
  volatile int* s_tile = reinterpret_cast<volatile int*>(sp + OFF_BAR + 192);
  volatile int* s_minfo = reinterpret_cast<volatile int*>(sp + OFF_BAR + 224);

  if (warp == 8) {
    if (lane == 0) {
      DBG_T(0);
      for (int i = 0; i < S; i++) { mbar_init(BAR(B_FULL + i), 1); mbar_init(BAR(B_EMPTY + i), 4); }
      mbar_init(BAR(B_WQ), 1); mbar_init(BAR(B_WO), 1);
      mbar_init(BAR(B_Q0), 4); mbar_init(BAR(B_QALL), 4);
      mbar_init(BAR(B_GATE), 1); mbar_init(BAR(B_UP), 1); mbar_init(BAR(B_DOWN), 1);
      mbar_init(BAR(B_W1FREE), 8);
      mbar_init(BAR(B_MFULL0), 4); mbar_init(BAR(B_MFULL1), 4);
      mbar_init(BAR(B_MFREE0), 4); mbar_init(BAR(B_MFREE1), 4);
      asm volatile("fence.proxy.async.shared::cta;" ::: "memory");
      if (cta < NJOB) {
        mbar_expect_tx(BAR(B_WQ), 576 * 64);
        for (int i = 0; i < 3; i++) tma2d(sb + OFF_W1 + i * 12288, &mapWq, cta * 32, i * 192, BAR(B_WQ));
      }
      for (int i = 0; i < S; i++) {
        const int tile = i * G + cta;
        s_tile[i] = tile;
        mbar_expect_tx(BAR(B_FULL + i), STAGE_BYTES);
        tma3d(sb + OFF_RING + i * STAGE_BYTES, &mapK, 0, tile * R, 0, BAR(B_FULL + i));
        tma3d(sb + OFF_RING + i * STAGE_BYTES + 8192, &mapV, 0, tile * R, 0, BAR(B_FULL + i));
      }
    }
    __syncthreads();
    if (lane == 0) {
      const unsigned ntd = NT - S * G;
      unsigned nxt = atomicAdd(&g_ticket, 1u);
      if (cta < NJOB) {
        mbar_expect_tx(BAR(B_WO), 32 * 1152);
        for (int i = 0; i < 32; i++)
          bulk_load(sb + OFF_W2 + i * ROWP, p.wo + (size_t)(cta * 32 + i) * D, 1152, BAR(B_WO));
        prefetch_map(&mapGate);
        prefetch_map(&mapUp);
      }
      int stage = 0;
      uint32_t ph = 0;
      while (true) {
        const unsigned d = nxt;
        if (d >= ntd) break;
        nxt = atomicAdd(&g_ticket, 1u);
        const int tile = S * G + (int)d;
        mbar_wait(BAR(B_EMPTY + stage), ph);
        s_tile[stage] = tile;
        mbar_expect_tx(BAR(B_FULL + stage), STAGE_BYTES);
        tma3d(sb + OFF_RING + stage * STAGE_BYTES, &mapK, 0, tile * R, 0, BAR(B_FULL + stage));
        tma3d(sb + OFF_RING + stage * STAGE_BYTES + 8192, &mapV, 0, tile * R, 0, BAR(B_FULL + stage));
        if (++stage == S) { stage = 0; ph ^= 1; }
      }
      DBG_T(1);
      const int ustart = 72 * (cta >> 1) + 40 * (cta & 1);
      if (cta < NJOB) {
        mbar_wait(BAR(B_W1FREE), 0);
        mbar_expect_tx(BAR(B_GATE), 576 * 80);
        for (int i = 0; i < 3; i++) tma2d(sb + OFF_W1 + i * 15360, &mapGate, ustart, i * 192, BAR(B_GATE));
        mbar_expect_tx(BAR(B_UP), 576 * 80);
        for (int i = 0; i < 3; i++) tma2d(sb + OFF_W1 + 46080 + i * 15360, &mapUp, ustart, i * 192, BAR(B_UP));
      }
      mbar_wait(BAR(B_EMPTY + stage), ph);
      s_tile[stage] = -1;
      mbar_arrive(BAR(B_FULL + stage));
      if (cta < NJOB) {
        for (int i = 1; i < S; i++) {
          if (++stage == S) { stage = 0; ph ^= 1; }
          mbar_wait(BAR(B_EMPTY + stage), ph);
        }
        const int nrows = (cta & 1) ? 32 : 40;
        mbar_expect_tx(BAR(B_DOWN), nrows * 1152);
        for (int i = 0; i < nrows; i++)
          bulk_load(sb + OFF_RING + i * ROWP, p.wdown + (size_t)(ustart + i) * D, 1152, BAR(B_DOWN));
      }
      DBG_T(2);
    }
    return;
  }

  __nv_bfloat16* xs = reinterpret_cast<__nv_bfloat16*>(sp + OFF_XS);
  __nv_bfloat16* vec = reinterpret_cast<__nv_bfloat16*>(sp + OFF_VEC);
  float* red = reinterpret_cast<float*>(sp + OFF_RED);
  __nv_bfloat16* smallv = reinterpret_cast<__nv_bfloat16*>(sp + OFF_SM);
  float* mbuf = reinterpret_cast<float*>(sp + OFF_MB);
  const bool has2 = tid < D - 512;
  unsigned tag;
  {
    Mod16<256> md;
    if (cta < NMODA) md.load(p.wmod, p.c, cta * 16, tid);
    tag = *(volatile unsigned*)&g_epoch + 1u;
    float xv[3];
#pragma unroll
    for (int k = 0; k < 3; k++) xv[k] = (k < 2 || has2) ? __bfloat162float(p.x[tid + 256 * k]) : 0.f;
    __syncthreads();
    const float mean = block_sum256(xv[0] + xv[1] + xv[2], red + 256, tid) * (1.f / D);
    const float d0 = xv[0] - mean, d1 = xv[1] - mean, d2 = has2 ? xv[2] - mean : 0.f;
    const float var = block_sum256(d0 * d0 + d1 * d1 + d2 * d2, red + 264, tid) * (1.f / D);
    const float mb = bfr(mean);
    const float den = bfr(sqrtf(bfr(bfr(var) + 1e-5f)));
    if (cta < NMODA) md.finish(cta * 16, tid, red, tag, 1);
    if (tid == 0) DBG_T(3);
    uint32_t sa[3], ca[3];
    unsigned n = 0;
    while (true) {
      bool ok = true;
#pragma unroll
      for (int k = 0; k < 3; k++) {
        if (k < 2 || has2) {
          sa[k] = ld_relaxed32(&g_mod[tid + 256 * k]);
          ca[k] = ld_relaxed32(&g_mod[D + tid + 256 * k]);
        } else {
          sa[k] = tag; ca[k] = tag;
        }
      }
#pragma unroll
      for (int k = 0; k < 3; k++) ok = ok && ok16(sa[k], tag) && ok16(ca[k], tag);
      if (ok) break;
      spin_check(n);
    }
#pragma unroll
    for (int k = 0; k < 3; k++) {
      if (k < 2 || has2) {
        const float nv = bfr(bfr(xv[k] - mb) / den);
        vec[tid + 256 * k] = __float2bfloat16_rn(bfr(nv * bfr(1.f + hi16(ca[k]))) + hi16(sa[k]));
        xs[tid + 256 * k] = __float2bfloat16_rn(xv[k]);
      }
    }
    named_sync(1, 256);
  }
  if (tid == 0) DBG_T(4);
  if (cta < NJOB) {
    mbar_wait(BAR(B_WQ), 0);
    float r = gemv32(sb + OFF_W1, vec, red, tid);
    float rn = __shfl_down_sync(0xffffffffu, r, 1);
    if (tid < 32 && (tid & 1) == 0) st_ll(&g_q[cta * 16 + (tid >> 1)], pack_bf2(r, rn), tag);
  }
  __syncwarp();
  if (lane == 0) mbar_arrive(BAR(B_W1FREE));

  if (warp < 4) {
    const int g = lane >> 2, t = lane & 3;
    const uint32_t* qs32 = reinterpret_cast<const uint32_t*>(sp + OFF_QS);
    uint32_t qf[16];
    float o[8][4];
    float m = -INFINITY, l = 0.f;
    int cur = -1, nflush = 0;
    const int key = warp * 8 + (lane & 7);
    uint32_t koff[4];
#pragma unroll
    for (int u = 0; u < 4; u++) {
      const int chunk = 4 * u + (lane >> 3);
      koff[u] = (chunk >> 3) * 4096 + key * 128 + (((chunk & 7) ^ (key & 7)) << 4);
    }
#pragma unroll
    for (int i = 0; i < 8; i++) { o[i][0] = o[i][1] = o[i][2] = o[i][3] = 0.f; }
#pragma unroll
    for (int i = 0; i < 16; i++) qf[i] = 0u;

    int stage = 0;
    uint32_t ph = 0;
    while (true) {
      mbar_wait(BAR(B_FULL + stage), ph);
      const int tile = s_tile[stage];
      const int head = (tile < 0) ? HKV : (tile >> TPH_SHIFT);
      if (head != cur) {
        if (cur >= 0 || head > 0) {
          const int pb = nflush & 1;
          if (nflush >= 2) mbar_wait(BAR(B_MFREE0 + pb), ((nflush >> 1) - 1) & 1);
          float* mb = mbuf + pb * MB_FLOATS + warp * 264;
          float lr = l;
          lr += __shfl_xor_sync(0xffffffffu, lr, 1);
          lr += __shfl_xor_sync(0xffffffffu, lr, 2);
          if (t == 0) {
#pragma unroll
            for (int i = 0; i < 8; i++) {
              mb[16 * i + g] = o[i][0];
              mb[132 + 16 * i + g] = o[i][1];
              mb[16 * i + 8 + g] = o[i][2];
              mb[132 + 16 * i + 8 + g] = o[i][3];
            }
            if (g < 2) { mb[g * 132 + 128] = m; mb[g * 132 + 129] = lr; }
          }
          if (warp == 0 && lane == 0) { s_minfo[pb * 2] = cur; s_minfo[pb * 2 + 1] = head; }
          __syncwarp();
          if (lane == 0) mbar_arrive(BAR(B_MFULL0 + pb));
          nflush++;
        }
        if (tile < 0) break;
        if (cur < 0 && tid == 0) DBG_T(13);
        cur = head;
        m = -INFINITY; l = 0.f;
#pragma unroll
        for (int i = 0; i < 8; i++) { o[i][0] = o[i][1] = o[i][2] = o[i][3] = 0.f; }
        mbar_wait(BAR(head < 2 ? B_Q0 : B_QALL), 0);
        if (g < 2) {
          const uint32_t* qh = qs32 + (2 * head + g) * 64;
#pragma unroll
          for (int s = 0; s < 8; s++) { qf[2 * s] = qh[8 * s + t]; qf[2 * s + 1] = qh[8 * s + 4 + t]; }
        }
        if (head == 0 && tid == 0) DBG_T(5);
      }
      const uint32_t kb = sb + OFF_RING + stage * STAGE_BYTES;
      uint32_t kr[16], vr[16];
#pragma unroll
      for (int u = 0; u < 4; u++) ldsm4(kb + koff[u], kr[4 * u], kr[4 * u + 1], kr[4 * u + 2], kr[4 * u + 3]);
#pragma unroll
      for (int u = 0; u < 4; u++) ldsm4t(kb + 8192 + koff[u], vr[4 * u], vr[4 * u + 1], vr[4 * u + 2], vr[4 * u + 3]);
      float sa[4] = {0.f, 0.f, 0.f, 0.f}, sbb[4] = {0.f, 0.f, 0.f, 0.f};
#pragma unroll
      for (int u = 0; u < 4; u++) {
        mma16816(sa, qf[4 * u], 0u, qf[4 * u + 1], 0u, kr[4 * u], kr[4 * u + 1]);
        mma16816(sbb, qf[4 * u + 2], 0u, qf[4 * u + 3], 0u, kr[4 * u + 2], kr[4 * u + 3]);
      }
      const float s0 = (sa[0] + sbb[0]) * SCALE_LOG2, s1 = (sa[1] + sbb[1]) * SCALE_LOG2;
      float tm = fmaxf(s0, s1);
      tm = fmaxf(tm, __shfl_xor_sync(0xffffffffu, tm, 1));
      tm = fmaxf(tm, __shfl_xor_sync(0xffffffffu, tm, 2));
      const float mn = fmaxf(m, tm);
      if (__any_sync(0xffffffffu, g < 2 && mn > m)) {
        const float alpha = ex2(m - mn);
        l *= alpha;
        const float a0 = __shfl_sync(0xffffffffu, alpha, 0), a1 = __shfl_sync(0xffffffffu, alpha, 4);
#pragma unroll
        for (int i = 0; i < 8; i++) { o[i][0] *= a0; o[i][1] *= a1; o[i][2] *= a0; o[i][3] *= a1; }
        m = mn;
      }
      float p0 = ex2(s0 - m), p1 = ex2(s1 - m);
      if (g >= 2) { p0 = 0.f; p1 = 0.f; }
      l += p0 + p1;
      const uint32_t pk = pack_bf2(p0, p1);
#pragma unroll
      for (int i = 0; i < 8; i++) mma1688(o[i], vr[2 * i], vr[2 * i + 1], pk);
      __syncwarp();
      if (lane == 0) mbar_arrive(BAR(B_EMPTY + stage));
      if (++stage == S) { stage = 0; ph ^= 1; }
    }
    __syncwarp();
    if (lane == 0) mbar_arrive(BAR(B_EMPTY + stage));
    if (tid == 0) DBG_T(6);
    if (cta >= NJOB) return;

    const bool two = tid < 16;
    const int c0 = 4 * tid, c1 = 512 + 4 * tid;
    uint4 ga0, sb0, cb0, ga1, sb1, cb1;
    {
      unsigned n = 0;
      while (true) {
        ga0 = ld_relaxed128(&g_mod[2 * D + c0]); sb0 = ld_relaxed128(&g_mod[3 * D + c0]); cb0 = ld_relaxed128(&g_mod[4 * D + c0]);
        bool ok = ok16(ga0, tag) && ok16(sb0, tag) && ok16(cb0, tag);
        if (two) {
          ga1 = ld_relaxed128(&g_mod[2 * D + c1]); sb1 = ld_relaxed128(&g_mod[3 * D + c1]); cb1 = ld_relaxed128(&g_mod[4 * D + c1]);
          ok = ok && ok16(ga1, tag) && ok16(sb1, tag) && ok16(cb1, tag);
        }
        if (ok) break;
        spin_check(n);
      }
    }
    if (lane == 0) wait_counter(&g_ydone, tag * (unsigned)(NJOB - 8));
    __syncwarp();
    float y0[4], y1[4] = {0.f, 0.f, 0.f, 0.f};
    {
      const uint4 a = ld_relaxed128(&g_yacc[c0]);
      y0[0] = __uint_as_float(a.x); y0[1] = __uint_as_float(a.y); y0[2] = __uint_as_float(a.z); y0[3] = __uint_as_float(a.w);
      if (two) {
        const uint4 b = ld_relaxed128(&g_yacc[c1]);
        y1[0] = __uint_as_float(b.x); y1[1] = __uint_as_float(b.y); y1[2] = __uint_as_float(b.z); y1[3] = __uint_as_float(b.w);
      }
    }
    if (tid == 0) DBG_T(14);
    {
      uint4 w[8];
      unsigned n = 0;
      while (true) {
        bool ok = true;
#pragma unroll
        for (int j = 0; j < 8; j++) w[j] = ld_relaxed128(&g_y15[j * D + c0]);
#pragma unroll
        for (int j = 0; j < 8; j++) ok = ok && ok2(w[j], tag);
        if (ok) break;
        spin_check(n);
      }
#pragma unroll
      for (int j = 0; j < 8; j++) {
        y0[0] += __uint_as_float(w[j].x); y0[1] += __uint_as_float(w[j].y);
        y0[2] += __uint_as_float(w[j].z); y0[3] += __uint_as_float(w[j].w);
      }
      if (two) {
        while (true) {
          bool ok = true;
#pragma unroll
          for (int j = 0; j < 8; j++) w[j] = ld_relaxed128(&g_y15[j * D + c1]);
#pragma unroll
          for (int j = 0; j < 8; j++) ok = ok && ok2(w[j], tag);
          if (ok) break;
          spin_check(n);
        }
#pragma unroll
        for (int j = 0; j < 8; j++) {
          y1[0] += __uint_as_float(w[j].x); y1[1] += __uint_as_float(w[j].y);
          y1[2] += __uint_as_float(w[j].z); y1[3] += __uint_as_float(w[j].w);
        }
      }
    }
    if (tid == 0) DBG_T(8);
    float x1a[4], x1b[4] = {0.f, 0.f, 0.f, 0.f};
    {
      const uint32_t gw0[4] = {ga0.x, ga0.y, ga0.z, ga0.w}, gw1[4] = {ga1.x, ga1.y, ga1.z, ga1.w};
#pragma unroll
      for (int j = 0; j < 4; j++) {
        x1a[j] = bfr(__bfloat162float(xs[c0 + j]) + bfr(hi16(gw0[j]) * bfr(y0[j])));
        if (two) x1b[j] = bfr(__bfloat162float(xs[c1 + j]) + bfr(hi16(gw1[j]) * bfr(y1[j])));
      }
    }
    float s = (x1a[0] + x1a[1]) + (x1a[2] + x1a[3]) + (x1b[0] + x1b[1]) + (x1b[2] + x1b[3]);
#pragma unroll
    for (int of = 16; of > 0; of >>= 1) s += __shfl_xor_sync(0xffffffffu, s, of);
    if (lane == 0) red[256 + warp] = s;
    named_sync(3, 128);
    const float mean = (red[256] + red[257] + red[258] + red[259]) * (1.f / D);
    float v = 0.f;
#pragma unroll
    for (int j = 0; j < 4; j++) {
      const float d = x1a[j] - mean;
      v += d * d;
      if (two) { const float e = x1b[j] - mean; v += e * e; }
    }
#pragma unroll
    for (int of = 16; of > 0; of >>= 1) v += __shfl_xor_sync(0xffffffffu, v, of);
    if (lane == 0) red[264 + warp] = v;
    named_sync(3, 128);
    const float var = (red[264] + red[265] + red[266] + red[267]) * (1.f / D);
    const float mb = bfr(mean);
    const float den = bfr(sqrtf(bfr(bfr(var) + 1e-5f)));
    {
      const uint32_t cw0[4] = {cb0.x, cb0.y, cb0.z, cb0.w}, sw0[4] = {sb0.x, sb0.y, sb0.z, sb0.w};
      const uint32_t cw1[4] = {cb1.x, cb1.y, cb1.z, cb1.w}, sw1[4] = {sb1.x, sb1.y, sb1.z, sb1.w};
#pragma unroll
      for (int j = 0; j < 4; j++) {
        const float nv = bfr(bfr(x1a[j] - mb) / den);
        vec[c0 + j] = __float2bfloat16_rn(bfr(nv * bfr(1.f + hi16(cw0[j]))) + hi16(sw0[j]));
        xs[c0 + j] = __float2bfloat16_rn(x1a[j]);
        if (two) {
          const float nw = bfr(bfr(x1b[j] - mb) / den);
          vec[c1 + j] = __float2bfloat16_rn(bfr(nw * bfr(1.f + hi16(cw1[j]))) + hi16(sw1[j]));
          xs[c1 + j] = __float2bfloat16_rn(x1b[j]);
        }
      }
    }
  } else {
    const int st = tid - 128, sw = warp - 4;
    if (cta == 0) {
      for (int i = st; i < D; i += 128) g_yacc[i] = 0.f;
      named_sync(2, 128);
      __threadfence();
    }
    {
      uint32_t* qs32 = reinterpret_cast<uint32_t*>(sp + OFF_QS);
      uint4 w[8];
#pragma unroll
      for (int k = 0; k < 8; k++) w[k] = ld_relaxed128(&g_q[(st + 128 * k) * 2]);
#pragma unroll
      for (int k = 0; k < 8; k++) {
        unsigned n = 0;
        while (w[k].y != tag || w[k].w != tag) {
          spin_check(n);
          w[k] = ld_relaxed128(&g_q[(st + 128 * k) * 2]);
        }
        *reinterpret_cast<uint2*>(qs32 + (st + 128 * k) * 2) = make_uint2(w[k].x, w[k].z);
        if (k == 0) {
          __syncwarp();
          if (lane == 0) mbar_arrive(BAR(B_Q0));
        }
      }
      __syncwarp();
      if (lane == 0) mbar_arrive(BAR(B_QALL));
    }
    for (int grp = cta; grp < NMODB; grp += G) {
      Mod16<128> md;
      md.load(p.wmod, p.c, 2 * D + grp * 16, st);
      named_sync(2, 128);
      md.finish(2 * D + grp * 16, st, red, tag, 2);
    }
    const int jobhead = (cta < NJOB) ? (cta >> 3) : -1;
    int nflush = 0;
    while (true) {
      const int pb = nflush & 1;
      mbar_wait(BAR(B_MFULL0 + pb), (nflush >> 1) & 1);
      const int from = s_minfo[pb * 2], to = s_minfo[pb * 2 + 1];
      if (from >= 0) {
        const float* mb = mbuf + pb * MB_FLOATS;
#pragma unroll
        for (int e = 0; e < 2; e++) {
          float mw[4], M = -INFINITY;
#pragma unroll
          for (int w = 0; w < 4; w++) { mw[w] = mb[w * 264 + e * 132 + 128]; M = fmaxf(M, mw[w]); }
          float acc = 0.f, L = 0.f;
#pragma unroll
          for (int w = 0; w < 4; w++) {
            const float f = ex2(mw[w] - M);
            acc += f * mb[w * 264 + e * 132 + st];
            L += f * mb[w * 264 + e * 132 + 129];
          }
          st_relaxed32(&g_recO[(((from * 2 + e) * 4 + sw) * MAXG + cta) * 32 + lane], tag2(acc, tag));
          if (st == 0) st_relaxed64v(&g_recML[((from * 2 + e) * MAXG + cta) * 2], tag2(M, tag), tag2(L, tag));
        }
      }
      for (int h = from + 1; h < to; h++) {
#pragma unroll
        for (int e = 0; e < 2; e++) {
          st_relaxed32(&g_recO[(((h * 2 + e) * 4 + sw) * MAXG + cta) * 32 + lane], tag2(0.f, tag));
          if (st == 0) st_relaxed64v(&g_recML[((h * 2 + e) * MAXG + cta) * 2], tag2(-1e30f, tag), tag2(0.f, tag));
        }
      }
      __syncwarp();
      if (lane == 0) mbar_arrive(BAR(B_MFREE0 + pb));
      nflush++;
      if (jobhead >= 0 && jobhead >= from && jobhead < to) {
        const int he = cta >> 2, rr = cta & 3;
        const int i4 = st & 7, cg = st >> 3;
        const float* rO = g_recO + (size_t)(he * 4 + rr) * MAXG * 32 + i4 * 4;
        const float* rML = g_recML + (size_t)he * MAXG * 2;
        uint4 ov[9];
        uint2 ml[9];
        {
          unsigned n = 0;
          while (true) {
            bool ok = true;
#pragma unroll
            for (int k = 0; k < 9; k++) {
              const int c = cg + 16 * k;
              if (c < G) {
                ov[k] = ld_relaxed128(rO + c * 32);
                ml[k] = ld_relaxed64v(rML + c * 2);
              } else {
                ov[k] = make_uint4(tag & 3u, tag & 3u, tag & 3u, tag & 3u);
                ml[k] = make_uint2(tag2(-1e30f, tag), tag & 3u);
              }
            }
#pragma unroll
            for (int k = 0; k < 9; k++) ok = ok && ok2(ov[k], tag) && ok2(ml[k].x, tag) && ok2(ml[k].y, tag);
            if (ok) break;
            spin_check(n);
          }
        }
        if (st == 0) DBG_T(15);
        float M = __uint_as_float(ml[0].x);
#pragma unroll
        for (int k = 1; k < 9; k++) M = fmaxf(M, __uint_as_float(ml[k].x));
        M = fmaxf(M, __shfl_xor_sync(0xffffffffu, M, 8));
        M = fmaxf(M, __shfl_xor_sync(0xffffffffu, M, 16));
        float4 acc = make_float4(0.f, 0.f, 0.f, 0.f);
        float L = 0.f;
#pragma unroll
        for (int k = 0; k < 9; k++) {
          const float f = ex2(__uint_as_float(ml[k].x) - M);
          acc.x += f * __uint_as_float(ov[k].x); acc.y += f * __uint_as_float(ov[k].y);
          acc.z += f * __uint_as_float(ov[k].z); acc.w += f * __uint_as_float(ov[k].w);
          L += f * __uint_as_float(ml[k].y);
        }
#pragma unroll
        for (int o = 8; o <= 16; o <<= 1) {
          acc.x += __shfl_xor_sync(0xffffffffu, acc.x, o); acc.y += __shfl_xor_sync(0xffffffffu, acc.y, o);
          acc.z += __shfl_xor_sync(0xffffffffu, acc.z, o); acc.w += __shfl_xor_sync(0xffffffffu, acc.w, o);
          L += __shfl_xor_sync(0xffffffffu, L, o);
        }
        if (lane < 8) {
          float* rp = red + 64 + sw * 40;
          rp[lane * 4] = acc.x; rp[lane * 4 + 1] = acc.y; rp[lane * 4 + 2] = acc.z; rp[lane * 4 + 3] = acc.w;
          if (lane == 0) { rp[32] = L; rp[33] = M; }
        }
        if (jobhead < HKV - 1) __threadfence();
        else if (cta == NJOB - 1 && st == 0)
          *(volatile unsigned*)&g_ticket = 0u;
        named_sync(2, 128);
        if (st < 32) {
          const float* rp = red + 64;
          const float MM = fmaxf(fmaxf(rp[33], rp[73]), fmaxf(rp[113], rp[153]));
          const float f0 = ex2(rp[33] - MM), f1 = ex2(rp[73] - MM), f2 = ex2(rp[113] - MM), f3 = ex2(rp[153] - MM);
          const float num = f0 * rp[st] + f1 * rp[40 + st] + f2 * rp[80 + st] + f3 * rp[120 + st];
          const float den = f0 * rp[32] + f1 * rp[72] + f2 * rp[112] + f3 * rp[152];
          smallv[st] = __float2bfloat16_rn(num / den);
        }
        named_sync(2, 128);
        mbar_wait(BAR(B_WO), 0);
        const int g = lane >> 2, t = lane & 3;
        const uint32_t* v32 = reinterpret_cast<const uint32_t*>(smallv);
        const uint32_t a0 = (g == 0) ? v32[t] : 0u, a1 = (g == 0) ? v32[4 + t] : 0u;
        const uint32_t a2 = (g == 0) ? v32[8 + t] : 0u, a3 = (g == 0) ? v32[12 + t] : 0u;
        const uint32_t rowaddr = sb + OFF_W2 + lane * ROWP;
        float* y15 = g_y15 + (cta & 7) * D;
#pragma unroll 6
        for (int c = sw * 18; c < sw * 18 + 18; c++) {
          uint32_t r0, r1, r2, r3;
          ldsm4t(rowaddr + c * 16, r0, r1, r2, r3);
          float acc4[4] = {0.f, 0.f, 0.f, 0.f};
          mma16816(acc4, a0, 0u, a1, 0u, r0, r1);
          mma16816(acc4, a2, 0u, a3, 0u, r2, r3);
          if (g == 0) {
            if (jobhead < HKV - 1) red_add2(g_yacc + c * 8 + 2 * t, acc4[0], acc4[1]);
            else st_relaxed64v(y15 + c * 8 + 2 * t, tag2(acc4[0], tag), tag2(acc4[1], tag));
          }
        }
        if (jobhead < HKV - 1) {
          named_sync(2, 128);
          if (st == 0) red_add_release(&g_ydone, 1u);
        }
        if (st == 0) DBG_T(7);
      }
      if (to >= HKV) break;
    }
    if (cta >= NJOB) return;
  }
  uint32_t gbw = 0;
  if (cta < NRED && tid < 8) {
    unsigned n = 0;
    gbw = ld_relaxed32(&g_mod[5 * D + cta * 8 + tid]);
    while (!ok16(gbw, tag)) { spin_check(n); gbw = ld_relaxed32(&g_mod[5 * D + cta * 8 + tid]); }
  }
  named_sync(1, 256);
  if (tid == 0) DBG_T(9);

  {
    const int g = lane >> 2, t = lane & 3, mi = lane >> 3;
    const int which = warp >> 2, kg = warp & 3;
    mbar_wait(BAR(which ? B_UP : B_GATE), 0);
    const uint32_t wb = sb + OFF_W1 + which * 46080;
    const uint32_t* v32 = reinterpret_cast<const uint32_t*>(vec);
    float acc[5][4];
#pragma unroll
    for (int n = 0; n < 5; n++) { acc[n][0] = acc[n][1] = acc[n][2] = acc[n][3] = 0.f; }
#pragma unroll
    for (int ks = 0; ks < 9; ks++) {
      const int k0 = (kg * 9 + ks) * 16;
      const uint32_t ra = wb + (k0 + (mi & 1) * 8 + (lane & 7)) * 80 + (mi >> 1) * 16;
      uint32_t r0, r1, r2, r3, r4, r5, r6, r7, r8, r9;
      ldsm4t(ra, r0, r1, r2, r3);
      ldsm4t(ra + 32, r4, r5, r6, r7);
      ldsm2t(wb + (k0 + (mi & 1) * 8 + (lane & 7)) * 80 + 64, r8, r9);
      const uint32_t a0 = (g == 0) ? v32[(k0 >> 1) + t] : 0u;
      const uint32_t a2 = (g == 0) ? v32[(k0 >> 1) + 4 + t] : 0u;
      mma16816(acc[0], a0, 0u, a2, 0u, r0, r1);
      mma16816(acc[1], a0, 0u, a2, 0u, r2, r3);
      mma16816(acc[2], a0, 0u, a2, 0u, r4, r5);
      mma16816(acc[3], a0, 0u, a2, 0u, r6, r7);
      mma16816(acc[4], a0, 0u, a2, 0u, r8, r9);
    }
    if (g == 0) {
#pragma unroll
      for (int n = 0; n < 5; n++) {
        red[warp * 40 + n * 8 + 2 * t] = acc[n][0];
        red[warp * 40 + n * 8 + 2 * t + 1] = acc[n][1];
      }
    }
    named_sync(1, 256);
    if (tid < 40) {
      const float gv = bfr(red[tid] + red[40 + tid] + red[80 + tid] + red[120 + tid]);
      const float uv = bfr(red[160 + tid] + red[200 + tid] + red[240 + tid] + red[280 + tid]);
      const float sg = bfr(gv / (1.f + __expf(-gv)));
      smallv[tid] = __float2bfloat16_rn(sg * uv);
    }
    named_sync(1, 256);
  }
  if (tid == 0) DBG_T(10);
  {
    const int g = lane >> 2, t = lane & 3;
    const bool k40 = (cta & 1) == 0;
    const uint32_t* v32 = reinterpret_cast<const uint32_t*>(smallv);
    const uint32_t a0 = (g == 0) ? v32[t] : 0u, a1 = (g == 0) ? v32[4 + t] : 0u;
    const uint32_t a2 = (g == 0) ? v32[8 + t] : 0u, a3 = (g == 0) ? v32[12 + t] : 0u;
    const uint32_t a4 = (g == 0) ? v32[16 + t] : 0u;
    mbar_wait(BAR(B_DOWN), 0);
    const uint32_t rowaddr = sb + OFF_RING + lane * ROWP;
    const uint32_t rowaddr2 = sb + OFF_RING + (32 + (lane & 7)) * ROWP;
    float* zp = g_z + (size_t)cta * D;
#pragma unroll
    for (int i = 0; i < 9; i++) {
      const int c = warp * 9 + i;
      uint32_t r0, r1, r2, r3;
      ldsm4t(rowaddr + c * 16, r0, r1, r2, r3);
      float acc4[4] = {0.f, 0.f, 0.f, 0.f};
      mma16816(acc4, a0, 0u, a1, 0u, r0, r1);
      mma16816(acc4, a2, 0u, a3, 0u, r2, r3);
      if (k40) {
        uint32_t r4;
        ldsm1t(rowaddr2 + c * 16, r4);
        mma1688(acc4, a4, 0u, r4);
      }
      if (g == 0) st_relaxed64v(zp + c * 8 + 2 * t, tag2(acc4[0], tag), tag2(acc4[1], tag));
    }
  }
  if (tid == 0) DBG_T(11);
  if (cta < NRED) {
    const int j = tid >> 1, hf = tid & 1;
    const float* zp = g_z + (size_t)j * D + cta * 8 + hf * 4;
    uint4 w = ld_relaxed128(zp);
    unsigned n = 0;
    while (!ok2(w, tag)) { spin_check(n); w = ld_relaxed128(zp); }
    float f0 = __uint_as_float(w.x), f1 = __uint_as_float(w.y), f2 = __uint_as_float(w.z), f3 = __uint_as_float(w.w);
#pragma unroll
    for (int o = 2; o <= 16; o <<= 1) {
      f0 += __shfl_xor_sync(0xffffffffu, f0, o); f1 += __shfl_xor_sync(0xffffffffu, f1, o);
      f2 += __shfl_xor_sync(0xffffffffu, f2, o); f3 += __shfl_xor_sync(0xffffffffu, f3, o);
    }
    float* rp = red + 320;
    if (lane < 2) {
      rp[warp * 8 + lane * 4] = f0; rp[warp * 8 + lane * 4 + 1] = f1;
      rp[warp * 8 + lane * 4 + 2] = f2; rp[warp * 8 + lane * 4 + 3] = f3;
    }
    named_sync(1, 256);
    if (tid < 8) {
      float s = 0.f;
#pragma unroll
      for (int w8 = 0; w8 < 8; w8++) s += rp[w8 * 8 + tid];
      const int col = cta * 8 + tid;
      p.out[col] = __float2bfloat16_rn(__bfloat162float(xs[col]) + bfr(hi16(gbw) * bfr(s)));
    }
    if (cta == 0 && tid == 0) *(volatile unsigned*)&g_epoch = tag;
  }
  if (tid == 0) DBG_T(12);
}

typedef CUresult (*EncodeFn)(CUtensorMap*, CUtensorMapDataType, cuuint32_t, void*, const cuuint64_t*, const cuuint64_t*,
                             const cuuint32_t*, const cuuint32_t*, CUtensorMapInterleave, CUtensorMapSwizzle,
                             CUtensorMapL2promotion, CUtensorMapFloatOOBfill);

CUtensorMap make_map(EncodeFn enc, const void* base, int rank, const cuuint64_t* dims, const cuuint64_t* strides,
                     const cuuint32_t* box, CUtensorMapSwizzle sw, CUtensorMapL2promotion pr) {
  CUtensorMap m;
  cuuint32_t es[3] = {1, 1, 1};
  enc(&m, CU_TENSOR_MAP_DATA_TYPE_BFLOAT16, rank, const_cast<void*>(base), dims, strides, box, es,
      CU_TENSOR_MAP_INTERLEAVE_NONE, sw, pr, CU_TENSOR_MAP_FLOAT_OOB_FILL_NONE);
  return m;
}

}

extern "C" void kernel_launch(void* const* d_in, const int* in_sizes, int n_in, void* d_out, int out_size) {
  (void)in_sizes; (void)n_in; (void)out_size;
  static EncodeFn enc = nullptr;
  static int nsm = 0;
  if (!enc) {
    void* fn = nullptr;
    cudaDriverEntryPointQueryResult qr;
    cudaGetDriverEntryPoint("cuTensorMapEncodeTiled", &fn, cudaEnableDefault, &qr);
    enc = (EncodeFn)fn;
    int dev = 0;
    cudaGetDevice(&dev);
    cudaDeviceGetAttribute(&nsm, cudaDevAttrMultiProcessorCount, dev);
    cudaFuncSetAttribute(fused_kernel, cudaFuncAttributeMaxDynamicSharedMemorySize, SMEM_BYTES);
  }
  CUtensorMap mK, mV, mWq, mG, mU;
  {
    cuuint64_t dims[3] = {64, (cuuint64_t)HKV * SK, 2};
    cuuint64_t str[2] = {256, 128};
    cuuint32_t box[3] = {64, R, 2};
    mK = make_map(enc, d_in[1], 3, dims, str, box, CU_TENSOR_MAP_SWIZZLE_128B, CU_TENSOR_MAP_L2_PROMOTION_L2_256B);
    mV = make_map(enc, d_in[2], 3, dims, str, box, CU_TENSOR_MAP_SWIZZLE_128B, CU_TENSOR_MAP_L2_PROMOTION_L2_256B);
  }
  {
    cuuint64_t dims[2] = {NQ, D};
    cuuint64_t str[1] = {NQ * 2};
    cuuint32_t box[2] = {32, 192};
    mWq = make_map(enc, d_in[3], 2, dims, str, box, CU_TENSOR_MAP_SWIZZLE_64B, CU_TENSOR_MAP_L2_PROMOTION_NONE);
  }
  {
    cuuint64_t dims[2] = {FF, D};
    cuuint64_t str[1] = {FF * 2};
    cuuint32_t box[2] = {40, 192};
    mG = make_map(enc, d_in[6], 2, dims, str, box, CU_TENSOR_MAP_SWIZZLE_NONE, CU_TENSOR_MAP_L2_PROMOTION_NONE);
    mU = make_map(enc, d_in[7], 2, dims, str, box, CU_TENSOR_MAP_SWIZZLE_NONE, CU_TENSOR_MAP_L2_PROMOTION_NONE);
  }
  Params p;
  p.x = (const __nv_bfloat16*)d_in[0];
  p.c = (const __nv_bfloat16*)d_in[9];
  p.wmod = (const __nv_bfloat16*)d_in[10];
  p.wo = (const __nv_bfloat16*)d_in[4];
  p.wdown = (const __nv_bfloat16*)d_in[8];
  p.out = (__nv_bfloat16*)d_out;
  int G = nsm < MAXG ? nsm : MAXG;
  fused_kernel<<<G, 288, SMEM_BYTES, cudaStreamPerThread>>>(mK, mV, mWq, mG, mU, p);
}
```

```cpp
#include <cuda_runtime.h>
#include <cuda_bf16.h>
#include <cuda.h>
#include <stdint.h>

namespace {

constexpr int D = 576, HKV = 16, SK = 65536, DH = 128, FF = 4608, NMOD = 6 * D, NQ = 4096;
constexpr int R = 32;
constexpr int TPH = SK / R;
constexpr int TPH_SHIFT = 11;
constexpr int NT = HKV * TPH;
constexpr int S = 5;
constexpr int STAGE_BYTES = 2 * R * DH * 2;
constexpr int MAXG = 144;
constexpr int NJOB = 128;
constexpr int NMODA = 2 * D / 16;
constexpr int NMODB = 4 * D / 16;
constexpr int NRED = D / 8;
constexpr int ROWP = 1168;

constexpr int OFF_RING = 0;
constexpr int OFF_W1 = OFF_RING + S * STAGE_BYTES;
constexpr int W1_BYTES = 2 * 576 * 80;
constexpr int OFF_W2 = OFF_W1 + W1_BYTES;
constexpr int W2_BYTES = 32 * ROWP;
constexpr int OFF_QS = OFF_W2 + W2_BYTES;
constexpr int OFF_MB = OFF_QS + NQ * 2;
constexpr int MB_FLOATS = 4 * 2 * 132;
constexpr int OFF_XS = OFF_MB + 2 * MB_FLOATS * 4;
constexpr int OFF_VEC = OFF_XS + D * 2;
constexpr int OFF_RED = OFF_VEC + D * 2;
constexpr int OFF_SM = OFF_RED + 384 * 4;
constexpr int OFF_BAR = OFF_SM + 128;
constexpr int SMEM_BYTES = OFF_BAR + 256;
static_assert(SMEM_BYTES <= 232448, "smem");
static_assert(40 * ROWP <= S * STAGE_BYTES, "down fits ring");

constexpr float SCALE_LOG2 = 0.08838834764831845f * 1.4426950408889634f;
constexpr unsigned SPIN_LIMIT = 1u << 22;

__device__ unsigned g_epoch;
__device__ unsigned g_ticket;
__device__ unsigned g_ydone;
__device__ __align__(16) uint32_t g_mod[NMOD];
__device__ __align__(16) unsigned long long g_q[NQ / 2];
__device__ __align__(16) float g_recO[HKV * 8 * MAXG * 32];
__device__ __align__(16) float g_recML[HKV * 2 * MAXG * 2];
__device__ __align__(16) float g_yacc[D];
__device__ __align__(16) float g_y15[8 * D];
__device__ __align__(16) float g_z[NJOB * D];

__device__ __forceinline__ uint32_t smem_u32(const void* p) { return (uint32_t)__cvta_generic_to_shared(p); }
__device__ __forceinline__ void mbar_init(uint32_t bar, uint32_t cnt) {
  asm volatile("mbarrier.init.shared::cta.b64 [%0], %1;" ::"r"(bar), "r"(cnt) : "memory");
}
__device__ __forceinline__ void mbar_expect_tx(uint32_t bar, uint32_t bytes) {
  asm volatile("mbarrier.arrive.expect_tx.shared::cta.b64 _, [%0], %1;" ::"r"(bar), "r"(bytes) : "memory");
}
__device__ __forceinline__ void mbar_arrive(uint32_t bar) {
  asm volatile("mbarrier.arrive.shared::cta.b64 _, [%0];" ::"r"(bar) : "memory");
}
__device__ __forceinline__ bool mbar_try(uint32_t bar, uint32_t parity) {
  uint32_t ok;
  asm volatile("{\n.reg .pred p;\nmbarrier.try_wait.parity.shared::cta.b64 p, [%1], %2;\nselp.u32 %0, 1, 0, p;\n}"
               : "=r"(ok) : "r"(bar), "r"(parity) : "memory");
  return ok != 0;
}
__device__ __forceinline__ void mbar_wait(uint32_t bar, uint32_t parity) {
  unsigned n = 0;
  while (!mbar_try(bar, parity)) {
    if (++n > SPIN_LIMIT) __trap();
  }
}
__device__ __forceinline__ void bulk_load(uint32_t dst, const void* src, uint32_t bytes, uint32_t bar) {
  asm volatile("cp.async.bulk.shared::cluster.global.mbarrier::complete_tx::bytes [%0], [%1], %2, [%3];"
               ::"r"(dst), "l"(src), "r"(bytes), "r"(bar) : "memory");
}
__device__ __forceinline__ void tma2d(uint32_t dst, const CUtensorMap* m, int c0, int c1, uint32_t bar) {
  asm volatile("cp.async.bulk.tensor.2d.shared::cluster.global.mbarrier::complete_tx::bytes [%0], [%1, {%3,%4}], [%2];"
               ::"r"(dst), "l"(m), "r"(bar), "r"(c0), "r"(c1) : "memory");
}
__device__ __forceinline__ void tma3d(uint32_t dst, const CUtensorMap* m, int c0, int c1, int c2, uint32_t bar) {
  asm volatile("cp.async.bulk.tensor.3d.shared::cluster.global.mbarrier::complete_tx::bytes [%0], [%1, {%3,%4,%5}], [%2];"
               ::"r"(dst), "l"(m), "r"(bar), "r"(c0), "r"(c1), "r"(c2) : "memory");
}
__device__ __forceinline__ void prefetch_map(const CUtensorMap* m) {
  asm volatile("prefetch.tensormap [%0];" ::"l"(m) : "memory");
}
__device__ __forceinline__ void named_sync(int id, int n) { asm volatile("bar.sync %0, %1;" ::"r"(id), "r"(n) : "memory"); }
__device__ __forceinline__ void ldsm4(uint32_t a, uint32_t& r0, uint32_t& r1, uint32_t& r2, uint32_t& r3) {
  asm volatile("ldmatrix.sync.aligned.m8n8.x4.shared.b16 {%0,%1,%2,%3}, [%4];"
               : "=r"(r0), "=r"(r1), "=r"(r2), "=r"(r3) : "r"(a) : "memory");
}
__device__ __forceinline__ void ldsm4t(uint32_t a, uint32_t& r0, uint32_t& r1, uint32_t& r2, uint32_t& r3) {
  asm volatile("ldmatrix.sync.aligned.m8n8.x4.trans.shared.b16 {%0,%1,%2,%3}, [%4];"
               : "=r"(r0), "=r"(r1), "=r"(r2), "=r"(r3) : "r"(a) : "memory");
}
__device__ __forceinline__ void ldsm2t(uint32_t a, uint32_t& r0, uint32_t& r1) {
  asm volatile("ldmatrix.sync.aligned.m8n8.x2.trans.shared.b16 {%0,%1}, [%2];"
               : "=r"(r0), "=r"(r1) : "r"(a) : "memory");
}
__device__ __forceinline__ void ldsm1t(uint32_t a, uint32_t& r0) {
  asm volatile("ldmatrix.sync.aligned.m8n8.x1.trans.shared.b16 {%0}, [%1];" : "=r"(r0) : "r"(a) : "memory");
}
__device__ __forceinline__ void mma16816(float (&c)[4], uint32_t a0, uint32_t a1, uint32_t a2, uint32_t a3,
                                         uint32_t b0, uint32_t b1) {
  asm volatile("mma.sync.aligned.m16n8k16.row.col.f32.bf16.bf16.f32 {%0,%1,%2,%3}, {%4,%5,%6,%7}, {%8,%9}, {%0,%1,%2,%3};"
               : "+f"(c[0]), "+f"(c[1]), "+f"(c[2]), "+f"(c[3])
               : "r"(a0), "r"(a1), "r"(a2), "r"(a3), "r"(b0), "r"(b1));
}
__device__ __forceinline__ void mma1688(float (&c)[4], uint32_t a0, uint32_t a1, uint32_t b0) {
  asm volatile("mma.sync.aligned.m16n8k8.row.col.f32.bf16.bf16.f32 {%0,%1,%2,%3}, {%4,%5}, {%6}, {%0,%1,%2,%3};"
               : "+f"(c[0]), "+f"(c[1]), "+f"(c[2]), "+f"(c[3])
               : "r"(a0), "r"(a1), "r"(b0));
}
__device__ __forceinline__ float bfr(float x) { return __bfloat162float(__float2bfloat16_rn(x)); }
__device__ __forceinline__ uint32_t pack_bf2(float lo, float hi) {
  uint32_t r;
  asm("cvt.rn.bf16x2.f32 %0, %1, %2;" : "=r"(r) : "f"(hi), "f"(lo));
  return r;
}
__device__ __forceinline__ float ex2(float x) {
  float r;
  asm("ex2.approx.ftz.f32 %0, %1;" : "=f"(r) : "f"(x));
  return r;
}
__device__ __forceinline__ void st_ll(unsigned long long* p, uint32_t v, uint32_t tag) {
  unsigned long long w = ((unsigned long long)tag << 32) | v;
  asm volatile("st.relaxed.gpu.global.b64 [%0], %1;" ::"l"(p), "l"(w) : "memory");
}
__device__ __forceinline__ uint32_t ld_relaxed32(const void* p) {
  uint32_t w;
  asm volatile("ld.relaxed.gpu.global.b32 %0, [%1];" : "=r"(w) : "l"(p) : "memory");
  return w;
}
__device__ __forceinline__ uint2 ld_relaxed64v(const void* p) {
  uint2 w;
  asm volatile("ld.relaxed.gpu.global.v2.b32 {%0,%1}, [%2];" : "=r"(w.x), "=r"(w.y) : "l"(p) : "memory");
  return w;
}
__device__ __forceinline__ uint4 ld_relaxed128(const void* p) {
  uint4 w;
  asm volatile("ld.relaxed.gpu.global.v4.b32 {%0,%1,%2,%3}, [%4];"
               : "=r"(w.x), "=r"(w.y), "=r"(w.z), "=r"(w.w) : "l"(p) : "memory");
  return w;
}
__device__ __forceinline__ void st_relaxed32(void* p, uint32_t v) {
  asm volatile("st.relaxed.gpu.global.b32 [%0], %1;" ::"l"(p), "r"(v) : "memory");
}
__device__ __forceinline__ void st_relaxed64v(void* p, uint32_t a, uint32_t b) {
  asm volatile("st.relaxed.gpu.global.v2.b32 [%0], {%1,%2};" ::"l"(p), "r"(a), "r"(b) : "memory");
}
__device__ __forceinline__ uint32_t tag2(float v, uint32_t tag) { return (__float_as_uint(v) & ~3u) | (tag & 3u); }
__device__ __forceinline__ bool ok2(uint32_t w, uint32_t tag) { return ((w ^ tag) & 3u) == 0u; }
__device__ __forceinline__ bool ok2(const uint4& w, uint32_t tag) {
  return (((w.x ^ tag) | (w.y ^ tag) | (w.z ^ tag) | (w.w ^ tag)) & 3u) == 0u;
}
__device__ __forceinline__ bool ok16(uint32_t w, uint32_t tag) { return ((w ^ tag) & 0xffffu) == 0u; }
__device__ __forceinline__ bool ok16(const uint4& w, uint32_t tag) {
  return (((w.x ^ tag) | (w.y ^ tag) | (w.z ^ tag) | (w.w ^ tag)) & 0xffffu) == 0u;
}
__device__ __forceinline__ float hi16(uint32_t w) { return __uint_as_float(w & 0xffff0000u); }
__device__ __forceinline__ void spin_check(unsigned& n) {
  if (++n > SPIN_LIMIT) __trap();
}
__device__ __forceinline__ uint4 ldg_nc128(const void* p) {
  uint4 w;
  asm volatile("ld.global.nc.L1::no_allocate.L2::256B.v4.b32 {%0,%1,%2,%3}, [%4];"
               : "=r"(w.x), "=r"(w.y), "=r"(w.z), "=r"(w.w) : "l"(p));
  return w;
}
__device__ __forceinline__ unsigned ld_acquire(const unsigned* p) {
  unsigned v;
  asm volatile("ld.acquire.gpu.global.u32 %0, [%1];" : "=r"(v) : "l"(p) : "memory");
  return v;
}
__device__ __forceinline__ void wait_counter(const unsigned* p, unsigned target) {
  unsigned n = 0;
  while (ld_acquire(p) != target) {
    __nanosleep(64);
    if (++n > SPIN_LIMIT) __trap();
  }
}
__device__ __forceinline__ void red_add_release(unsigned* p, unsigned v) {
  asm volatile("red.release.gpu.global.add.u32 [%0], %1;" ::"l"(p), "r"(v) : "memory");
}
__device__ __forceinline__ void red_add2(float* p, float a, float b) {
  asm volatile("red.relaxed.gpu.global.add.v2.f32 [%0], {%1,%2};" ::"l"(p), "f"(a), "f"(b) : "memory");
}
#define DBG_T(i) do { } while (0)

__device__ __forceinline__ float block_sum256(float v, float* red, int tid) {
#pragma unroll
  for (int o = 16; o > 0; o >>= 1) v += __shfl_xor_sync(0xffffffffu, v, o);
  if ((tid & 31) == 0) red[tid >> 5] = v;
  named_sync(1, 256);
  float s = 0.f;
#pragma unroll
  for (int i = 0; i < 8; i++) s += red[i];
  return s;
}

template <int NT>
struct Mod16 {
  static constexpr int RP = NT / 2;
  static constexpr int NP = (D + RP - 1) / RP;
  uint4 w[NP];
  float cv[NP];
  __device__ __forceinline__ void load(const __nv_bfloat16* wmod, const __nv_bfloat16* c, int col0, int t) {
#pragma unroll
    for (int i = 0; i < NP; i++) {
      const int row = (t >> 1) + RP * i;
      w[i] = make_uint4(0u, 0u, 0u, 0u);
      cv[i] = 0.f;
      if (row < D) {
        w[i] = ldg_nc128(wmod + (size_t)row * NMOD + col0 + (t & 1) * 8);
        cv[i] = __bfloat162float(c[row]);
      }
    }
  }
  __device__ __forceinline__ void finish(int col0, int t, float* red, uint32_t tag, int barid) {
    float acc[8];
#pragma unroll
    for (int j = 0; j < 8; j++) acc[j] = 0.f;
#pragma unroll
    for (int i = 0; i < NP; i++) {
      const float s = bfr(cv[i] / (1.f + __expf(-cv[i])));
      const uint32_t ww[4] = {w[i].x, w[i].y, w[i].z, w[i].w};
#pragma unroll
      for (int j = 0; j < 4; j++) {
        acc[2 * j] += s * __uint_as_float(ww[j] << 16);
        acc[2 * j + 1] += s * __uint_as_float(ww[j] & 0xffff0000u);
      }
    }
#pragma unroll
    for (int o = 2; o <= 16; o <<= 1)
#pragma unroll
      for (int j = 0; j < 8; j++) acc[j] += __shfl_xor_sync(0xffffffffu, acc[j], o);
    if ((t & 31) < 2) {
#pragma unroll
      for (int j = 0; j < 8; j++) red[(t >> 5) * 16 + (t & 1) * 8 + j] = acc[j];
    }
    named_sync(barid, NT);
    if (t < 16) {
      float r = 0.f;
#pragma unroll
      for (int wv = 0; wv < NT / 32; wv++) r += red[wv * 16 + t];
      st_relaxed32(&g_mod[col0 + t], (__float_as_uint(bfr(r)) & 0xffff0000u) | (tag & 0xffffu));
    }
  }
};

__device__ __forceinline__ float gemv32(uint32_t wbase, const __nv_bfloat16* vec, float* red, int tid) {
  const int warp = tid >> 5, lane = tid & 31, g = lane >> 2, t = lane & 3;
  const int np = warp & 1, kg = warp >> 1;
  const int mi = lane >> 3;
  float c0[4] = {0.f, 0.f, 0.f, 0.f}, c1[4] = {0.f, 0.f, 0.f, 0.f};
  const uint32_t* v32 = reinterpret_cast<const uint32_t*>(vec);
#pragma unroll
  for (int ks = 0; ks < 9; ks++) {
    const int k0 = (kg * 9 + ks) * 16;
    const int row = k0 + (mi & 1) * 8 + (lane & 7);
    const int chunk = 2 * np + (mi >> 1);
    uint32_t r0, r1, r2, r3;
    ldsm4t(wbase + row * 64 + ((chunk ^ ((row >> 1) & 3)) << 4), r0, r1, r2, r3);
    uint32_t a0 = (g == 0) ? v32[(k0 >> 1) + t] : 0u;
    uint32_t a2 = (g == 0) ? v32[(k0 >> 1) + 4 + t] : 0u;
    mma16816(c0, a0, 0u, a2, 0u, r0, r1);
    mma16816(c1, a0, 0u, a2, 0u, r2, r3);
  }
  if (g == 0) {
    float* rp = red + kg * 32 + np * 16 + 2 * t;
    rp[0] = c0[0]; rp[1] = c0[1]; rp[8] = c1[0]; rp[9] = c1[1];
  }
  named_sync(1, 256);
  float r = 0.f;
  if (tid < 32) r = red[tid] + red[32 + tid] + red[64 + tid] + red[96 + tid];
  return r;
}

struct Params {
  const __nv_bfloat16* x;
  const __nv_bfloat16* c;
  const __nv_bfloat16* wmod;
  const __nv_bfloat16* wo;
  const __nv_bfloat16* wdown;
  __nv_bfloat16* out;
};

enum { B_FULL = 0, B_EMPTY = S, B_WQ = 2 * S, B_Q0, B_QALL, B_WO, B_GATE, B_UP, B_DOWN, B_W1FREE, B_MFULL0, B_MFULL1,
       B_MFREE0, B_MFREE1, B_COUNT };
static_assert(B_COUNT * 8 <= 192, "barrier area");

__global__ void __launch_bounds__(288, 1)
fused_kernel(const __grid_constant__ CUtensorMap mapK, const __grid_constant__ CUtensorMap mapV,
             const __grid_constant__ CUtensorMap mapWq, const __grid_constant__ CUtensorMap mapGate,
             const __grid_constant__ CUtensorMap mapUp, const Params p) {
  extern __shared__ __align__(1024) unsigned char sp[];
  const uint32_t sb = smem_u32(sp);
  if (sb & 1023u) __trap();
  const int tid = threadIdx.x, warp = tid >> 5, lane = tid & 31;
  const int cta = blockIdx.x, G = gridDim.x;
  const uint32_t bar0 = sb + OFF_BAR;
  auto BAR = [&](int i) { return bar0 + 8u * i; };
  volatile int* s_tile = reinterpret_cast<volatile int*>(sp + OFF_BAR + 192);
  volatile int* s_minfo = reinterpret_cast<volatile int*>(sp + OFF_BAR + 224);

  if (warp == 8) {
    if (lane == 0) {
      DBG_T(0);
      for (int i = 0; i < S; i++) { mbar_init(BAR(B_FULL + i), 1); mbar_init(BAR(B_EMPTY + i), 4); }
      mbar_init(BAR(B_WQ), 1); mbar_init(BAR(B_WO), 1);
      mbar_init(BAR(B_Q0), 4); mbar_init(BAR(B_QALL), 4);
      mbar_init(BAR(B_GATE), 1); mbar_init(BAR(B_UP), 1); mbar_init(BAR(B_DOWN), 1);
      mbar_init(BAR(B_W1FREE), 8);
      mbar_init(BAR(B_MFULL0), 4); mbar_init(BAR(B_MFULL1), 4);
      mbar_init(BAR(B_MFREE0), 4); mbar_init(BAR(B_MFREE1), 4);
      asm volatile("fence.proxy.async.shared::cta;" ::: "memory");
    }
    __syncthreads();
    if (lane == 0) {
      if (cta < NJOB) {
        mbar_expect_tx(BAR(B_WQ), 576 * 64);
        for (int i = 0; i < 3; i++) tma2d(sb + OFF_W1 + i * 12288, &mapWq, cta * 32, i * 192, BAR(B_WQ));
      }
      for (int i = 0; i < S; i++) {
        const int tile = i * G + cta;
        s_tile[i] = tile;
        mbar_expect_tx(BAR(B_FULL + i), STAGE_BYTES);
        tma3d(sb + OFF_RING + i * STAGE_BYTES, &mapK, 0, tile * R, 0, BAR(B_FULL + i));
        tma3d(sb + OFF_RING + i * STAGE_BYTES + 8192, &mapV, 0, tile * R, 0, BAR(B_FULL + i));
      }
      DBG_T(23);
      const unsigned ntd = NT - S * G;
      unsigned nxt = atomicAdd(&g_ticket, 1u);
      if (cta < NJOB) {
        mbar_expect_tx(BAR(B_WO), 32 * 1152);
        for (int i = 0; i < 32; i++)
          bulk_load(sb + OFF_W2 + i * ROWP, p.wo + (size_t)(cta * 32 + i) * D, 1152, BAR(B_WO));
        prefetch_map(&mapGate);
        prefetch_map(&mapUp);
      }
      int stage = 0;
      uint32_t ph = 0;
      while (true) {
        const unsigned d = nxt;
        if (d >= ntd) break;
        nxt = atomicAdd(&g_ticket, 1u);
        const int tile = S * G + (int)d;
        mbar_wait(BAR(B_EMPTY + stage), ph);
        s_tile[stage] = tile;
        mbar_expect_tx(BAR(B_FULL + stage), STAGE_BYTES);
        tma3d(sb + OFF_RING + stage * STAGE_BYTES, &mapK, 0, tile * R, 0, BAR(B_FULL + stage));
        tma3d(sb + OFF_RING + stage * STAGE_BYTES + 8192, &mapV, 0, tile * R, 0, BAR(B_FULL + stage));
        if (++stage == S) { stage = 0; ph ^= 1; }
      }
      DBG_T(1);
      const int ustart = 72 * (cta >> 1) + 40 * (cta & 1);
      if (cta < NJOB) {
        mbar_wait(BAR(B_W1FREE), 0);
        mbar_expect_tx(BAR(B_GATE), 576 * 80);
        for (int i = 0; i < 3; i++) tma2d(sb + OFF_W1 + i * 15360, &mapGate, ustart, i * 192, BAR(B_GATE));
        mbar_expect_tx(BAR(B_UP), 576 * 80);
        for (int i = 0; i < 3; i++) tma2d(sb + OFF_W1 + 46080 + i * 15360, &mapUp, ustart, i * 192, BAR(B_UP));
      }
      mbar_wait(BAR(B_EMPTY + stage), ph);
      s_tile[stage] = -1;
      mbar_arrive(BAR(B_FULL + stage));
      if (cta < NJOB) {
        for (int i = 1; i < S; i++) {
          if (++stage == S) { stage = 0; ph ^= 1; }
          mbar_wait(BAR(B_EMPTY + stage), ph);
        }
        const int nrows = (cta & 1) ? 32 : 40;
        mbar_expect_tx(BAR(B_DOWN), nrows * 1152);
        for (int i = 0; i < nrows; i++)
          bulk_load(sb + OFF_RING + i * ROWP, p.wdown + (size_t)(ustart + i) * D, 1152, BAR(B_DOWN));
      }
      DBG_T(2);
    }
    return;
  }

  __nv_bfloat16* xs = reinterpret_cast<__nv_bfloat16*>(sp + OFF_XS);
  __nv_bfloat16* vec = reinterpret_cast<__nv_bfloat16*>(sp + OFF_VEC);
  float* red = reinterpret_cast<float*>(sp + OFF_RED);
  __nv_bfloat16* smallv = reinterpret_cast<__nv_bfloat16*>(sp + OFF_SM);
  float* mbuf = reinterpret_cast<float*>(sp + OFF_MB);
  const bool has2 = tid < D - 512;
  unsigned tag;
  {
    Mod16<256> md;
    if (cta < NMODA) md.load(p.wmod, p.c, cta * 16, tid);
    tag = *(volatile unsigned*)&g_epoch + 1u;
    float xv[3];
#pragma unroll
    for (int k = 0; k < 3; k++) xv[k] = (k < 2 || has2) ? __bfloat162float(p.x[tid + 256 * k]) : 0.f;
    __syncthreads();
    const float mean = block_sum256(xv[0] + xv[1] + xv[2], red + 256, tid) * (1.f / D);
    const float d0 = xv[0] - mean, d1 = xv[1] - mean, d2 = has2 ? xv[2] - mean : 0.f;
    const float var = block_sum256(d0 * d0 + d1 * d1 + d2 * d2, red + 264, tid) * (1.f / D);
    const float mb = bfr(mean);
    const float den = bfr(sqrtf(bfr(bfr(var) + 1e-5f)));
    if (cta < NMODA) md.finish(cta * 16, tid, red, tag, 1);
    if (tid == 0) DBG_T(3);
    uint32_t sa[3], ca[3];
    unsigned n = 0;
    while (true) {
      bool ok = true;
#pragma unroll
      for (int k = 0; k < 3; k++) {
        if (k < 2 || has2) {
          sa[k] = ld_relaxed32(&g_mod[tid + 256 * k]);
          ca[k] = ld_relaxed32(&g_mod[D + tid + 256 * k]);
        } else {
          sa[k] = tag; ca[k] = tag;
        }
      }
#pragma unroll
      for (int k = 0; k < 3; k++) ok = ok && ok16(sa[k], tag) && ok16(ca[k], tag);
      if (ok) break;
      spin_check(n);
    }
#pragma unroll
    for (int k = 0; k < 3; k++) {
      if (k < 2 || has2) {
        const float nv = bfr(bfr(xv[k] - mb) / den);
        vec[tid + 256 * k] = __float2bfloat16_rn(bfr(nv * bfr(1.f + hi16(ca[k]))) + hi16(sa[k]));
        xs[tid + 256 * k] = __float2bfloat16_rn(xv[k]);
      }
    }
    named_sync(1, 256);
  }
  if (tid == 0) DBG_T(4);
  if (cta < NJOB) {
    mbar_wait(BAR(B_WQ), 0);
    float r = gemv32(sb + OFF_W1, vec, red, tid);
    float rn = __shfl_down_sync(0xffffffffu, r, 1);
    if (tid < 32 && (tid & 1) == 0) st_ll(&g_q[cta * 16 + (tid >> 1)], pack_bf2(r, rn), tag);
  }
  __syncwarp();
  if (lane == 0) mbar_arrive(BAR(B_W1FREE));

  if (warp < 4) {
    const int g = lane >> 2, t = lane & 3;
    const uint32_t* qs32 = reinterpret_cast<const uint32_t*>(sp + OFF_QS);
    uint32_t qf[16];
    float o[8][4];
    float m = -INFINITY, l = 0.f;
    int cur = -1, nflush = 0;
    const int key = warp * 8 + (lane & 7);
    uint32_t koff[4];
#pragma unroll
    for (int u = 0; u < 4; u++) {
      const int chunk = 4 * u + (lane >> 3);
      koff[u] = (chunk >> 3) * 4096 + key * 128 + (((chunk & 7) ^ (key & 7)) << 4);
    }
#pragma unroll
    for (int i = 0; i < 8; i++) { o[i][0] = o[i][1] = o[i][2] = o[i][3] = 0.f; }
#pragma unroll
    for (int i = 0; i < 16; i++) qf[i] = 0u;

    int stage = 0;
    uint32_t ph = 0;
    while (true) {
      mbar_wait(BAR(B_FULL + stage), ph);
      const int tile = s_tile[stage];
      const int head = (tile < 0) ? HKV : (tile >> TPH_SHIFT);
      if (head != cur) {
        if (cur >= 0 || head > 0) {
          const int pb = nflush & 1;
          if (nflush >= 2) mbar_wait(BAR(B_MFREE0 + pb), ((nflush >> 1) - 1) & 1);
          float* mb = mbuf + pb * MB_FLOATS + warp * 264;
          float lr = l;
          lr += __shfl_xor_sync(0xffffffffu, lr, 1);
          lr += __shfl_xor_sync(0xffffffffu, lr, 2);
          if (t == 0) {
#pragma unroll
            for (int i = 0; i < 8; i++) {
              mb[16 * i + g] = o[i][0];
              mb[132 + 16 * i + g] = o[i][1];
              mb[16 * i + 8 + g] = o[i][2];
              mb[132 + 16 * i + 8 + g] = o[i][3];
            }
            if (g < 2) { mb[g * 132 + 128] = m; mb[g * 132 + 129] = lr; }
          }
          if (warp == 0 && lane == 0) { s_minfo[pb * 2] = cur; s_minfo[pb * 2 + 1] = head; }
          __syncwarp();
          if (lane == 0) mbar_arrive(BAR(B_MFULL0 + pb));
          nflush++;
        }
        if (tile < 0) break;
        if (cur < 0 && tid == 0) DBG_T(13);
        cur = head;
        m = -INFINITY; l = 0.f;
#pragma unroll
        for (int i = 0; i < 8; i++) { o[i][0] = o[i][1] = o[i][2] = o[i][3] = 0.f; }
        mbar_wait(BAR(head < 2 ? B_Q0 : B_QALL), 0);
        if (g < 2) {
          const uint32_t* qh = qs32 + (2 * head + g) * 64;
#pragma unroll
          for (int s = 0; s < 8; s++) { qf[2 * s] = qh[8 * s + t]; qf[2 * s + 1] = qh[8 * s + 4 + t]; }
        }
        if (head == 0 && tid == 0) DBG_T(5);
      }
      const uint32_t kb = sb + OFF_RING + stage * STAGE_BYTES;
      uint32_t kr[16], vr[16];
#pragma unroll
      for (int u = 0; u < 4; u++) ldsm4(kb + koff[u], kr[4 * u], kr[4 * u + 1], kr[4 * u + 2], kr[4 * u + 3]);
#pragma unroll
      for (int u = 0; u < 4; u++) ldsm4t(kb + 8192 + koff[u], vr[4 * u], vr[4 * u + 1], vr[4 * u + 2], vr[4 * u + 3]);
      float sa[4] = {0.f, 0.f, 0.f, 0.f}, sbb[4] = {0.f, 0.f, 0.f, 0.f};
#pragma unroll
      for (int u = 0; u < 4; u++) {
        mma16816(sa, qf[4 * u], 0u, qf[4 * u + 1], 0u, kr[4 * u], kr[4 * u + 1]);
        mma16816(sbb, qf[4 * u + 2], 0u, qf[4 * u + 3], 0u, kr[4 * u + 2], kr[4 * u + 3]);
      }
      const float s0 = (sa[0] + sbb[0]) * SCALE_LOG2, s1 = (sa[1] + sbb[1]) * SCALE_LOG2;
      float tm = fmaxf(s0, s1);
      tm = fmaxf(tm, __shfl_xor_sync(0xffffffffu, tm, 1));
      tm = fmaxf(tm, __shfl_xor_sync(0xffffffffu, tm, 2));
      const float mn = fmaxf(m, tm);
      if (__any_sync(0xffffffffu, g < 2 && mn > m)) {
        const float alpha = ex2(m - mn);
        l *= alpha;
        const float a0 = __shfl_sync(0xffffffffu, alpha, 0), a1 = __shfl_sync(0xffffffffu, alpha, 4);
#pragma unroll
        for (int i = 0; i < 8; i++) { o[i][0] *= a0; o[i][1] *= a1; o[i][2] *= a0; o[i][3] *= a1; }
        m = mn;
      }
      float p0 = ex2(s0 - m), p1 = ex2(s1 - m);
      if (g >= 2) { p0 = 0.f; p1 = 0.f; }
      l += p0 + p1;
      const uint32_t pk = pack_bf2(p0, p1);
#pragma unroll
      for (int i = 0; i < 8; i++) mma1688(o[i], vr[2 * i], vr[2 * i + 1], pk);
      __syncwarp();
      if (lane == 0) mbar_arrive(BAR(B_EMPTY + stage));
      if (++stage == S) { stage = 0; ph ^= 1; }
    }
    __syncwarp();
    if (lane == 0) mbar_arrive(BAR(B_EMPTY + stage));
    if (tid == 0) DBG_T(6);
    if (cta >= NJOB) return;

    const bool two = tid < 16;
    const int c0 = 4 * tid, c1 = 512 + 4 * tid;
    uint4 ga0, sb0, cb0, ga1, sb1, cb1;
    {
      unsigned n = 0;
      while (true) {
        ga0 = ld_relaxed128(&g_mod[2 * D + c0]); sb0 = ld_relaxed128(&g_mod[3 * D + c0]); cb0 = ld_relaxed128(&g_mod[4 * D + c0]);
        bool ok = ok16(ga0, tag) && ok16(sb0, tag) && ok16(cb0, tag);
        if (two) {
          ga1 = ld_relaxed128(&g_mod[2 * D + c1]); sb1 = ld_relaxed128(&g_mod[3 * D + c1]); cb1 = ld_relaxed128(&g_mod[4 * D + c1]);
          ok = ok && ok16(ga1, tag) && ok16(sb1, tag) && ok16(cb1, tag);
        }
        if (ok) break;
        spin_check(n);
      }
    }
    if (lane == 0) wait_counter(&g_ydone, tag * (unsigned)(NJOB - 8));
    __syncwarp();
    float y0[4], y1[4] = {0.f, 0.f, 0.f, 0.f};
    {
      const uint4 a = ld_relaxed128(&g_yacc[c0]);
      y0[0] = __uint_as_float(a.x); y0[1] = __uint_as_float(a.y); y0[2] = __uint_as_float(a.z); y0[3] = __uint_as_float(a.w);
      if (two) {
        const uint4 b = ld_relaxed128(&g_yacc[c1]);
        y1[0] = __uint_as_float(b.x); y1[1] = __uint_as_float(b.y); y1[2] = __uint_as_float(b.z); y1[3] = __uint_as_float(b.w);
      }
    }
    if (tid == 0) DBG_T(14);
    {
      uint4 w[8];
      unsigned n = 0;
      while (true) {
        bool ok = true;
#pragma unroll
        for (int j = 0; j < 8; j++) w[j] = ld_relaxed128(&g_y15[j * D + c0]);
#pragma unroll
        for (int j = 0; j < 8; j++) ok = ok && ok2(w[j], tag);
        if (ok) break;
        spin_check(n);
      }
#pragma unroll
      for (int j = 0; j < 8; j++) {
        y0[0] += __uint_as_float(w[j].x); y0[1] += __uint_as_float(w[j].y);
        y0[2] += __uint_as_float(w[j].z); y0[3] += __uint_as_float(w[j].w);
      }
      if (two) {
        while (true) {
          bool ok = true;
#pragma unroll
          for (int j = 0; j < 8; j++) w[j] = ld_relaxed128(&g_y15[j * D + c1]);
#pragma unroll
          for (int j = 0; j < 8; j++) ok = ok && ok2(w[j], tag);
          if (ok) break;
          spin_check(n);
        }
#pragma unroll
        for (int j = 0; j < 8; j++) {
          y1[0] += __uint_as_float(w[j].x); y1[1] += __uint_as_float(w[j].y);
          y1[2] += __uint_as_float(w[j].z); y1[3] += __uint_as_float(w[j].w);
        }
      }
    }
    if (tid == 0) DBG_T(8);
    float x1a[4], x1b[4] = {0.f, 0.f, 0.f, 0.f};
    {
      const uint32_t gw0[4] = {ga0.x, ga0.y, ga0.z, ga0.w}, gw1[4] = {ga1.x, ga1.y, ga1.z, ga1.w};
#pragma unroll
      for (int j = 0; j < 4; j++) {
        x1a[j] = bfr(__bfloat162float(xs[c0 + j]) + bfr(hi16(gw0[j]) * bfr(y0[j])));
        if (two) x1b[j] = bfr(__bfloat162float(xs[c1 + j]) + bfr(hi16(gw1[j]) * bfr(y1[j])));
      }
    }
    float s = (x1a[0] + x1a[1]) + (x1a[2] + x1a[3]) + (x1b[0] + x1b[1]) + (x1b[2] + x1b[3]);
#pragma unroll
    for (int of = 16; of > 0; of >>= 1) s += __shfl_xor_sync(0xffffffffu, s, of);
    if (lane == 0) red[256 + warp] = s;
    named_sync(3, 128);
    const float mean = (red[256] + red[257] + red[258] + red[259]) * (1.f / D);
    float v = 0.f;
#pragma unroll
    for (int j = 0; j < 4; j++) {
      const float d = x1a[j] - mean;
      v += d * d;
      if (two) { const float e = x1b[j] - mean; v += e * e; }
    }
#pragma unroll
    for (int of = 16; of > 0; of >>= 1) v += __shfl_xor_sync(0xffffffffu, v, of);
    if (lane == 0) red[264 + warp] = v;
    named_sync(3, 128);
    const float var = (red[264] + red[265] + red[266] + red[267]) * (1.f / D);
    const float mb = bfr(mean);
    const float den = bfr(sqrtf(bfr(bfr(var) + 1e-5f)));
    {
      const uint32_t cw0[4] = {cb0.x, cb0.y, cb0.z, cb0.w}, sw0[4] = {sb0.x, sb0.y, sb0.z, sb0.w};
      const uint32_t cw1[4] = {cb1.x, cb1.y, cb1.z, cb1.w}, sw1[4] = {sb1.x, sb1.y, sb1.z, sb1.w};
#pragma unroll
      for (int j = 0; j < 4; j++) {
        const float nv = bfr(bfr(x1a[j] - mb) / den);
        vec[c0 + j] = __float2bfloat16_rn(bfr(nv * bfr(1.f + hi16(cw0[j]))) + hi16(sw0[j]));
        xs[c0 + j] = __float2bfloat16_rn(x1a[j]);
        if (two) {
          const float nw = bfr(bfr(x1b[j] - mb) / den);
          vec[c1 + j] = __float2bfloat16_rn(bfr(nw * bfr(1.f + hi16(cw1[j]))) + hi16(sw1[j]));
          xs[c1 + j] = __float2bfloat16_rn(x1b[j]);
        }
      }
    }
  } else {
    const int st = tid - 128, sw = warp - 4;
    if (cta == 0) {
      for (int i = st; i < D; i += 128) g_yacc[i] = 0.f;
      named_sync(2, 128);
      __threadfence();
    }
    {
      uint32_t* qs32 = reinterpret_cast<uint32_t*>(sp + OFF_QS);
      uint4 w[8];
#pragma unroll
      for (int k = 0; k < 8; k++) w[k] = ld_relaxed128(&g_q[(st + 128 * k) * 2]);
#pragma unroll
      for (int k = 0; k < 8; k++) {
        unsigned n = 0;
        while (w[k].y != tag || w[k].w != tag) {
          spin_check(n);
          w[k] = ld_relaxed128(&g_q[(st + 128 * k) * 2]);
        }
        *reinterpret_cast<uint2*>(qs32 + (st + 128 * k) * 2) = make_uint2(w[k].x, w[k].z);
        if (k == 0) {
          __syncwarp();
          if (lane == 0) mbar_arrive(BAR(B_Q0));
        }
      }
      __syncwarp();
      if (lane == 0) mbar_arrive(BAR(B_QALL));
    }
    for (int grp = cta; grp < NMODB; grp += G) {
      Mod16<128> md;
      md.load(p.wmod, p.c, 2 * D + grp * 16, st);
      named_sync(2, 128);
      md.finish(2 * D + grp * 16, st, red, tag, 2);
    }
    const int jobhead = (cta < NJOB) ? (cta >> 3) : -1;
    int nflush = 0;
    while (true) {
      const int pb = nflush & 1;
      mbar_wait(BAR(B_MFULL0 + pb), (nflush >> 1) & 1);
      const int from = s_minfo[pb * 2], to = s_minfo[pb * 2 + 1];
      if (from >= 0) {
        const float* mb = mbuf + pb * MB_FLOATS;
#pragma unroll
        for (int e = 0; e < 2; e++) {
          float mw[4], M = -INFINITY;
#pragma unroll
          for (int w = 0; w < 4; w++) { mw[w] = mb[w * 264 + e * 132 + 128]; M = fmaxf(M, mw[w]); }
          float acc = 0.f, L = 0.f;
#pragma unroll
          for (int w = 0; w < 4; w++) {
            const float f = ex2(mw[w] - M);
            acc += f * mb[w * 264 + e * 132 + st];
            L += f * mb[w * 264 + e * 132 + 129];
          }
          st_relaxed32(&g_recO[(((from * 2 + e) * 4 + sw) * MAXG + cta) * 32 + lane], tag2(acc, tag));
          if (st == 0) st_relaxed64v(&g_recML[((from * 2 + e) * MAXG + cta) * 2], tag2(M, tag), tag2(L, tag));
        }
      }
      for (int h = from + 1; h < to; h++) {
#pragma unroll
        for (int e = 0; e < 2; e++) {
          st_relaxed32(&g_recO[(((h * 2 + e) * 4 + sw) * MAXG + cta) * 32 + lane], tag2(0.f, tag));
          if (st == 0) st_relaxed64v(&g_recML[((h * 2 + e) * MAXG + cta) * 2], tag2(-1e30f, tag), tag2(0.f, tag));
        }
      }
      __syncwarp();
      if (lane == 0) mbar_arrive(BAR(B_MFREE0 + pb));
      nflush++;
      if (jobhead >= 0 && jobhead >= from && jobhead < to) {
        const int he = cta >> 2, rr = cta & 3;
        const int i4 = st & 7, cg = st >> 3;
        const float* rO = g_recO + (size_t)(he * 4 + rr) * MAXG * 32 + i4 * 4;
        const float* rML = g_recML + (size_t)he * MAXG * 2;
        uint4 ov[9];
        uint2 ml[9];
        {
          unsigned n = 0;
          while (true) {
            bool ok = true;
#pragma unroll
            for (int k = 0; k < 9; k++) {
              const int c = cg + 16 * k;
              if (c < G) {
                ov[k] = ld_relaxed128(rO + c * 32);
                ml[k] = ld_relaxed64v(rML + c * 2);
              } else {
                ov[k] = make_uint4(tag & 3u, tag & 3u, tag & 3u, tag & 3u);
                ml[k] = make_uint2(tag2(-1e30f, tag), tag & 3u);
              }
            }
#pragma unroll
            for (int k = 0; k < 9; k++) ok = ok && ok2(ov[k], tag) && ok2(ml[k].x, tag) && ok2(ml[k].y, tag);
            if (ok) break;
            spin_check(n);
          }
        }
        if (st == 0) DBG_T(15);
        float M = __uint_as_float(ml[0].x);
#pragma unroll
        for (int k = 1; k < 9; k++) M = fmaxf(M, __uint_as_float(ml[k].x));
        M = fmaxf(M, __shfl_xor_sync(0xffffffffu, M, 8));
        M = fmaxf(M, __shfl_xor_sync(0xffffffffu, M, 16));
        float4 acc = make_float4(0.f, 0.f, 0.f, 0.f);
        float L = 0.f;
#pragma unroll
        for (int k = 0; k < 9; k++) {
          const float f = ex2(__uint_as_float(ml[k].x) - M);
          acc.x += f * __uint_as_float(ov[k].x); acc.y += f * __uint_as_float(ov[k].y);
          acc.z += f * __uint_as_float(ov[k].z); acc.w += f * __uint_as_float(ov[k].w);
          L += f * __uint_as_float(ml[k].y);
        }
#pragma unroll
        for (int o = 8; o <= 16; o <<= 1) {
          acc.x += __shfl_xor_sync(0xffffffffu, acc.x, o); acc.y += __shfl_xor_sync(0xffffffffu, acc.y, o);
          acc.z += __shfl_xor_sync(0xffffffffu, acc.z, o); acc.w += __shfl_xor_sync(0xffffffffu, acc.w, o);
          L += __shfl_xor_sync(0xffffffffu, L, o);
        }
        if (lane < 8) {
          float* rp = red + 64 + sw * 40;
          rp[lane * 4] = acc.x; rp[lane * 4 + 1] = acc.y; rp[lane * 4 + 2] = acc.z; rp[lane * 4 + 3] = acc.w;
          if (lane == 0) { rp[32] = L; rp[33] = M; }
        }
        if (jobhead < HKV - 1) __threadfence();
        else if (cta == NJOB - 1 && st == 0)
          *(volatile unsigned*)&g_ticket = 0u;
        named_sync(2, 128);
        if (st < 32) {
          const float* rp = red + 64;
          const float MM = fmaxf(fmaxf(rp[33], rp[73]), fmaxf(rp[113], rp[153]));
          const float f0 = ex2(rp[33] - MM), f1 = ex2(rp[73] - MM), f2 = ex2(rp[113] - MM), f3 = ex2(rp[153] - MM);
          const float num = f0 * rp[st] + f1 * rp[40 + st] + f2 * rp[80 + st] + f3 * rp[120 + st];
          const float den = f0 * rp[32] + f1 * rp[72] + f2 * rp[112] + f3 * rp[152];
          smallv[st] = __float2bfloat16_rn(num / den);
        }
        named_sync(2, 128);
        mbar_wait(BAR(B_WO), 0);
        const int g = lane >> 2, t = lane & 3;
        const uint32_t* v32 = reinterpret_cast<const uint32_t*>(smallv);
        const uint32_t a0 = (g == 0) ? v32[t] : 0u, a1 = (g == 0) ? v32[4 + t] : 0u;
        const uint32_t a2 = (g == 0) ? v32[8 + t] : 0u, a3 = (g == 0) ? v32[12 + t] : 0u;
        const uint32_t rowaddr = sb + OFF_W2 + lane * ROWP;
        float* y15 = g_y15 + (cta & 7) * D;
#pragma unroll 6
        for (int c = sw * 18; c < sw * 18 + 18; c++) {
          uint32_t r0, r1, r2, r3;
          ldsm4t(rowaddr + c * 16, r0, r1, r2, r3);
          float acc4[4] = {0.f, 0.f, 0.f, 0.f};
          mma16816(acc4, a0, 0u, a1, 0u, r0, r1);
          mma16816(acc4, a2, 0u, a3, 0u, r2, r3);
          if (g == 0) {
            if (jobhead < HKV - 1) red_add2(g_yacc + c * 8 + 2 * t, acc4[0], acc4[1]);
            else st_relaxed64v(y15 + c * 8 + 2 * t, tag2(acc4[0], tag), tag2(acc4[1], tag));
          }
        }
        if (jobhead < HKV - 1) {
          named_sync(2, 128);
          if (st == 0) red_add_release(&g_ydone, 1u);
        }
        if (st == 0) DBG_T(7);
      }
      if (to >= HKV) break;
    }
    if (cta >= NJOB) return;
  }
  uint32_t gbw = 0;
  if (cta < NRED && tid < 8) {
    unsigned n = 0;
    gbw = ld_relaxed32(&g_mod[5 * D + cta * 8 + tid]);
    while (!ok16(gbw, tag)) { spin_check(n); gbw = ld_relaxed32(&g_mod[5 * D + cta * 8 + tid]); }
  }
  named_sync(1, 256);
  if (tid == 0) DBG_T(9);

  {
    const int g = lane >> 2, t = lane & 3, mi = lane >> 3;
    const int which = warp >> 2, kg = warp & 3;
    mbar_wait(BAR(which ? B_UP : B_GATE), 0);
    const uint32_t wb = sb + OFF_W1 + which * 46080;
    const uint32_t* v32 = reinterpret_cast<const uint32_t*>(vec);
    float acc[5][4];
#pragma unroll
    for (int n = 0; n < 5; n++) { acc[n][0] = acc[n][1] = acc[n][2] = acc[n][3] = 0.f; }
#pragma unroll
    for (int ks = 0; ks < 9; ks++) {
      const int k0 = (kg * 9 + ks) * 16;
      const uint32_t ra = wb + (k0 + (mi & 1) * 8 + (lane & 7)) * 80 + (mi >> 1) * 16;
      uint32_t r0, r1, r2, r3, r4, r5, r6, r7, r8, r9;
      ldsm4t(ra, r0, r1, r2, r3);
      ldsm4t(ra + 32, r4, r5, r6, r7);
      ldsm2t(wb + (k0 + (mi & 1) * 8 + (lane & 7)) * 80 + 64, r8, r9);
      const uint32_t a0 = (g == 0) ? v32[(k0 >> 1) + t] : 0u;
      const uint32_t a2 = (g == 0) ? v32[(k0 >> 1) + 4 + t] : 0u;
      mma16816(acc[0], a0, 0u, a2, 0u, r0, r1);
      mma16816(acc[1], a0, 0u, a2, 0u, r2, r3);
      mma16816(acc[2], a0, 0u, a2, 0u, r4, r5);
      mma16816(acc[3], a0, 0u, a2, 0u, r6, r7);
      mma16816(acc[4], a0, 0u, a2, 0u, r8, r9);
    }
    if (g == 0) {
#pragma unroll
      for (int n = 0; n < 5; n++) {
        red[warp * 40 + n * 8 + 2 * t] = acc[n][0];
        red[warp * 40 + n * 8 + 2 * t + 1] = acc[n][1];
      }
    }
    named_sync(1, 256);
    if (tid < 40) {
      const float gv = bfr(red[tid] + red[40 + tid] + red[80 + tid] + red[120 + tid]);
      const float uv = bfr(red[160 + tid] + red[200 + tid] + red[240 + tid] + red[280 + tid]);
      const float sg = bfr(gv / (1.f + __expf(-gv)));
      smallv[tid] = __float2bfloat16_rn(sg * uv);
    }
    named_sync(1, 256);
  }
  if (tid == 0) DBG_T(10);
  {
    const int g = lane >> 2, t = lane & 3;
    const bool k40 = (cta & 1) == 0;
    const uint32_t* v32 = reinterpret_cast<const uint32_t*>(smallv);
    const uint32_t a0 = (g == 0) ? v32[t] : 0u, a1 = (g == 0) ? v32[4 + t] : 0u;
    const uint32_t a2 = (g == 0) ? v32[8 + t] : 0u, a3 = (g == 0) ? v32[12 + t] : 0u;
    const uint32_t a4 = (g == 0) ? v32[16 + t] : 0u;
    mbar_wait(BAR(B_DOWN), 0);
    const uint32_t rowaddr = sb + OFF_RING + lane * ROWP;
    const uint32_t rowaddr2 = sb + OFF_RING + (32 + (lane & 7)) * ROWP;
    float* zp = g_z + (size_t)cta * D;
#pragma unroll
    for (int i = 0; i < 9; i++) {
      const int c = warp * 9 + i;
      uint32_t r0, r1, r2, r3;
      ldsm4t(rowaddr + c * 16, r0, r1, r2, r3);
      float acc4[4] = {0.f, 0.f, 0.f, 0.f};
      mma16816(acc4, a0, 0u, a1, 0u, r0, r1);
      mma16816(acc4, a2, 0u, a3, 0u, r2, r3);
      if (k40) {
        uint32_t r4;
        ldsm1t(rowaddr2 + c * 16, r4);
        mma1688(acc4, a4, 0u, r4);
      }
      if (g == 0) st_relaxed64v(zp + c * 8 + 2 * t, tag2(acc4[0], tag), tag2(acc4[1], tag));
    }
  }
  if (tid == 0) DBG_T(11);
  if (cta < NRED) {
    const int j = tid >> 1, hf = tid & 1;
    const float* zp = g_z + (size_t)j * D + cta * 8 + hf * 4;
    uint4 w = ld_relaxed128(zp);
    unsigned n = 0;
    while (!ok2(w, tag)) { spin_check(n); w = ld_relaxed128(zp); }
    float f0 = __uint_as_float(w.x), f1 = __uint_as_float(w.y), f2 = __uint_as_float(w.z), f3 = __uint_as_float(w.w);
#pragma unroll
    for (int o = 2; o <= 16; o <<= 1) {
      f0 += __shfl_xor_sync(0xffffffffu, f0, o); f1 += __shfl_xor_sync(0xffffffffu, f1, o);
      f2 += __shfl_xor_sync(0xffffffffu, f2, o); f3 += __shfl_xor_sync(0xffffffffu, f3, o);
    }
    float* rp = red + 320;
    if (lane < 2) {
      rp[warp * 8 + lane * 4] = f0; rp[warp * 8 + lane * 4 + 1] = f1;
      rp[warp * 8 + lane * 4 + 2] = f2; rp[warp * 8 + lane * 4 + 3] = f3;
    }
    named_sync(1, 256);
    if (tid < 8) {
      float s = 0.f;
#pragma unroll
      for (int w8 = 0; w8 < 8; w8++) s += rp[w8 * 8 + tid];
      const int col = cta * 8 + tid;
      p.out[col] = __float2bfloat16_rn(__bfloat162float(xs[col]) + bfr(hi16(gbw) * bfr(s)));
    }
    if (cta == 0 && tid == 0) *(volatile unsigned*)&g_epoch = tag;
  }
  if (tid == 0) DBG_T(12);
}

typedef CUresult (*EncodeFn)(CUtensorMap*, CUtensorMapDataType, cuuint32_t, void*, const cuuint64_t*, const cuuint64_t*,
                             const cuuint32_t*, const cuuint32_t*, CUtensorMapInterleave, CUtensorMapSwizzle,
                             CUtensorMapL2promotion, CUtensorMapFloatOOBfill);

CUtensorMap make_map(EncodeFn enc, const void* base, int rank, const cuuint64_t* dims, const cuuint64_t* strides,
                     const cuuint32_t* box, CUtensorMapSwizzle sw, CUtensorMapL2promotion pr) {
  CUtensorMap m;
  cuuint32_t es[3] = {1, 1, 1};
  enc(&m, CU_TENSOR_MAP_DATA_TYPE_BFLOAT16, rank, const_cast<void*>(base), dims, strides, box, es,
      CU_TENSOR_MAP_INTERLEAVE_NONE, sw, pr, CU_TENSOR_MAP_FLOAT_OOB_FILL_NONE);
  return m;
}

}

extern "C" void kernel_launch(void* const* d_in, const int* in_sizes, int n_in, void* d_out, int out_size) {
  (void)in_sizes; (void)n_in; (void)out_size;
  static EncodeFn enc = nullptr;
  static int nsm = 0;
  if (!enc) {
    void* fn = nullptr;
    cudaDriverEntryPointQueryResult qr;
    cudaGetDriverEntryPoint("cuTensorMapEncodeTiled", &fn, cudaEnableDefault, &qr);
    enc = (EncodeFn)fn;
    int dev = 0;
    cudaGetDevice(&dev);
    cudaDeviceGetAttribute(&nsm, cudaDevAttrMultiProcessorCount, dev);
    cudaFuncSetAttribute(fused_kernel, cudaFuncAttributeMaxDynamicSharedMemorySize, SMEM_BYTES);
  }
  CUtensorMap mK, mV, mWq, mG, mU;
  {
    cuuint64_t dims[3] = {64, (cuuint64_t)HKV * SK, 2};
    cuuint64_t str[2] = {256, 128};
    cuuint32_t box[3] = {64, R, 2};
    mK = make_map(enc, d_in[1], 3, dims, str, box, CU_TENSOR_MAP_SWIZZLE_128B, CU_TENSOR_MAP_L2_PROMOTION_L2_256B);
    mV = make_map(enc, d_in[2], 3, dims, str, box, CU_TENSOR_MAP_SWIZZLE_128B, CU_TENSOR_MAP_L2_PROMOTION_L2_256B);
  }
  {
    cuuint64_t dims[2] = {NQ, D};
    cuuint64_t str[1] = {NQ * 2};
    cuuint32_t box[2] = {32, 192};
    mWq = make_map(enc, d_in[3], 2, dims, str, box, CU_TENSOR_MAP_SWIZZLE_64B, CU_TENSOR_MAP_L2_PROMOTION_L2_256B);
  }
  {
    cuuint64_t dims[2] = {FF, D};
    cuuint64_t str[1] = {FF * 2};
    cuuint32_t box[2] = {40, 192};
    mG = make_map(enc, d_in[6], 2, dims, str, box, CU_TENSOR_MAP_SWIZZLE_NONE, CU_TENSOR_MAP_L2_PROMOTION_L2_256B);
    mU = make_map(enc, d_in[7], 2, dims, str, box, CU_TENSOR_MAP_SWIZZLE_NONE, CU_TENSOR_MAP_L2_PROMOTION_L2_256B);
  }
  Params p;
  p.x = (const __nv_bfloat16*)d_in[0];
  p.c = (const __nv_bfloat16*)d_in[9];
  p.wmod = (const __nv_bfloat16*)d_in[10];
  p.wo = (const __nv_bfloat16*)d_in[4];
  p.wdown = (const __nv_bfloat16*)d_in[8];
  p.out = (__nv_bfloat16*)d_out;
  int G = nsm < MAXG ? nsm : MAXG;
  fused_kernel<<<G, 288, SMEM_BYTES, cudaStreamPerThread>>>(mK, mV, mWq, mG, mU, p);
}
```

```cpp
#include <cuda_runtime.h>
#include <cuda_bf16.h>
#include <cuda.h>
#include <stdint.h>

namespace {

constexpr int D = 576, HKV = 16, SK = 65536, DH = 128, FF = 4608, NMOD = 6 * D, NQ = 4096;
constexpr int R = 32;
constexpr int TPH = SK / R;
constexpr int TPH_SHIFT = 11;
constexpr int NT = HKV * TPH;
constexpr int S = 5;
constexpr int STAGE_BYTES = 2 * R * DH * 2;
constexpr int MAXG = 144;
constexpr int NJOB = 128;
constexpr int NMODA = 72;
constexpr int NREP = 8;
constexpr int NQ0 = 16;
constexpr int NMODB = 72;
constexpr int NRED = D / 8;
constexpr int NEARLY = NJOB - 8;
constexpr int ROWP = 1168;

constexpr int OFF_RING = 0;
constexpr int OFF_W1 = OFF_RING + S * STAGE_BYTES;
constexpr int W1_BYTES = 2 * 576 * 80;
constexpr int OFF_W2 = OFF_W1 + W1_BYTES;
constexpr int W2_BYTES = 32 * ROWP;
constexpr int OFF_UP = OFF_W1 + W1_BYTES / 2;
constexpr int OFF_QS = OFF_W2 + W2_BYTES;
constexpr int OFF_MB = OFF_QS + NQ * 2;
constexpr int MB_FLOATS = 4 * 2 * 132;
constexpr int OFF_SC = OFF_MB + 2 * MB_FLOATS * 4;
constexpr int OFF_VEC = OFF_SC + D * 2;
constexpr int OFF_RED = OFF_VEC + D * 2;
constexpr int OFF_SM = OFF_RED + 384 * 4;
constexpr int OFF_BAR = OFF_SM + 128;
constexpr int SMEM_BYTES = OFF_BAR + 384;
static_assert(SMEM_BYTES <= 232448, "smem");
static_assert(40 * ROWP <= S * STAGE_BYTES, "down fits ring");
static_assert(OFF_QS % 512 == 0 && OFF_W1 % 512 == 0, "swizzle alignment");

constexpr float SCALE = 0.08838834764831845f;
constexpr float LOG2E = 1.4426950408889634f;
#define TBATCH 1u
#define TEND 8u
#define HW 2
constexpr unsigned SPIN_LIMIT = 1u << 22;

__device__ unsigned g_epoch;
__device__ unsigned g_ticket;
__device__ __align__(128) unsigned g_modA[NREP * 2 * D];
__device__ __align__(128) float g_modB[4 * D];
__device__ __align__(128) unsigned long long g_q[NQ / 2];
__device__ __align__(128) unsigned long long g_q0[NREP * NQ0 * 16];
__device__ __align__(128) unsigned g_flag[NREP * 32];
__device__ __align__(128) float g_recO[HKV * 8 * MAXG * 32];
__device__ __align__(16) float g_recML[HKV * 2 * MAXG * 2];
__device__ __align__(128) float g_yp[NJOB * D];
__device__ __align__(128) float g_ye[NREP * D];
__device__ __align__(128) float g_z[NJOB * D];

__device__ __forceinline__ uint32_t smem_u32(const void* p) { return (uint32_t)__cvta_generic_to_shared(p); }
__device__ __forceinline__ void mbar_init(uint32_t bar, uint32_t cnt) {
  asm volatile("mbarrier.init.shared::cta.b64 [%0], %1;" ::"r"(bar), "r"(cnt) : "memory");
}
__device__ __forceinline__ void mbar_expect_tx(uint32_t bar, uint32_t bytes) {
  asm volatile("mbarrier.arrive.expect_tx.shared::cta.b64 _, [%0], %1;" ::"r"(bar), "r"(bytes) : "memory");
}
__device__ __forceinline__ void mbar_arrive(uint32_t bar) {
  asm volatile("mbarrier.arrive.shared::cta.b64 _, [%0];" ::"r"(bar) : "memory");
}
__device__ __forceinline__ bool mbar_try(uint32_t bar, uint32_t parity) {
  uint32_t ok;
  asm volatile("{\n.reg .pred p;\nmbarrier.try_wait.parity.shared::cta.b64 p, [%1], %2;\nselp.u32 %0, 1, 0, p;\n}"
               : "=r"(ok) : "r"(bar), "r"(parity) : "memory");
  return ok != 0;
}
__device__ __forceinline__ void mbar_wait(uint32_t bar, uint32_t parity) {
  unsigned n = 0;
  while (!mbar_try(bar, parity)) {
    if (++n > SPIN_LIMIT) __trap();
  }
}
__device__ __forceinline__ uint64_t stream_policy() {
  uint64_t pol;
  asm volatile("createpolicy.fractional.L2::evict_first.b64 %0, 1.0;" : "=l"(pol));
  return pol;
}
__device__ __forceinline__ void bulk_load(uint32_t dst, const void* src, uint32_t bytes, uint32_t bar, uint64_t pol) {
  asm volatile("cp.async.bulk.shared::cluster.global.mbarrier::complete_tx::bytes.L2::cache_hint [%0], [%1], %2, [%3], %4;"
               ::"r"(dst), "l"(src), "r"(bytes), "r"(bar), "l"(pol) : "memory");
}
__device__ __forceinline__ void tma2d(uint32_t dst, const CUtensorMap* m, int c0, int c1, uint32_t bar, uint64_t pol) {
  asm volatile("cp.async.bulk.tensor.2d.shared::cluster.global.mbarrier::complete_tx::bytes.L2::cache_hint"
               " [%0], [%1, {%3,%4}], [%2], %5;"
               ::"r"(dst), "l"(m), "r"(bar), "r"(c0), "r"(c1), "l"(pol) : "memory");
}
__device__ __forceinline__ void tma3d(uint32_t dst, const CUtensorMap* m, int c0, int c1, int c2, uint32_t bar,
                                      uint64_t pol) {
  asm volatile("cp.async.bulk.tensor.3d.shared::cluster.global.mbarrier::complete_tx::bytes.L2::cache_hint"
               " [%0], [%1, {%3,%4,%5}], [%2], %6;"
               ::"r"(dst), "l"(m), "r"(bar), "r"(c0), "r"(c1), "r"(c2), "l"(pol) : "memory");
}
__device__ __forceinline__ void prefetch_map(const CUtensorMap* m) {
  asm volatile("prefetch.tensormap [%0];" ::"l"(m) : "memory");
}
__device__ __forceinline__ void named_sync(int id, int n) { asm volatile("bar.sync %0, %1;" ::"r"(id), "r"(n) : "memory"); }
__device__ __forceinline__ void ldsm4(uint32_t a, uint32_t& r0, uint32_t& r1, uint32_t& r2, uint32_t& r3) {
  asm volatile("ldmatrix.sync.aligned.m8n8.x4.shared.b16 {%0,%1,%2,%3}, [%4];"
               : "=r"(r0), "=r"(r1), "=r"(r2), "=r"(r3) : "r"(a) : "memory");
}
__device__ __forceinline__ void ldsm4t(uint32_t a, uint32_t& r0, uint32_t& r1, uint32_t& r2, uint32_t& r3) {
  asm volatile("ldmatrix.sync.aligned.m8n8.x4.trans.shared.b16 {%0,%1,%2,%3}, [%4];"
               : "=r"(r0), "=r"(r1), "=r"(r2), "=r"(r3) : "r"(a) : "memory");
}
__device__ __forceinline__ void ldsm2t(uint32_t a, uint32_t& r0, uint32_t& r1) {
  asm volatile("ldmatrix.sync.aligned.m8n8.x2.trans.shared.b16 {%0,%1}, [%2];"
               : "=r"(r0), "=r"(r1) : "r"(a) : "memory");
}
__device__ __forceinline__ void mma16816(float (&c)[4], uint32_t a0, uint32_t a1, uint32_t a2, uint32_t a3,
                                         uint32_t b0, uint32_t b1) {
  asm volatile("mma.sync.aligned.m16n8k16.row.col.f32.bf16.bf16.f32 {%0,%1,%2,%3}, {%4,%5,%6,%7}, {%8,%9}, {%0,%1,%2,%3};"
               : "+f"(c[0]), "+f"(c[1]), "+f"(c[2]), "+f"(c[3])
               : "r"(a0), "r"(a1), "r"(a2), "r"(a3), "r"(b0), "r"(b1));
}
__device__ __forceinline__ void mma1688(float (&c)[4], uint32_t a0, uint32_t a1, uint32_t b0) {
  asm volatile("mma.sync.aligned.m16n8k8.row.col.f32.bf16.bf16.f32 {%0,%1,%2,%3}, {%4,%5}, {%6}, {%0,%1,%2,%3};"
               : "+f"(c[0]), "+f"(c[1]), "+f"(c[2]), "+f"(c[3])
               : "r"(a0), "r"(a1), "r"(b0));
}
__device__ __forceinline__ uint32_t pack_bf2(float lo, float hi) {
  uint32_t r;
  asm("cvt.rn.bf16x2.f32 %0, %1, %2;" : "=r"(r) : "f"(hi), "f"(lo));
  return r;
}
__device__ __forceinline__ float bfr(float x) { return __uint_as_float(pack_bf2(0.f, x)); }
__device__ __forceinline__ float bf_lo(uint32_t w) { return __uint_as_float(w << 16); }
__device__ __forceinline__ float bf_hi(uint32_t w) { return __uint_as_float(w & 0xffff0000u); }
__device__ __forceinline__ float ex2(float x) {
  float r;
  asm("ex2.approx.ftz.f32 %0, %1;" : "=f"(r) : "f"(x));
  return r;
}
__device__ __forceinline__ float fsqrt(float x) {
  float r;
  asm("sqrt.approx.f32 %0, %1;" : "=f"(r) : "f"(x));
  return r;
}
__device__ __forceinline__ float silu(float x) { return __fdividef(x, 1.f + __expf(-x)); }
__device__ __forceinline__ void st_ll(unsigned long long* p, uint32_t v, uint32_t tag) {
  unsigned long long w = ((unsigned long long)tag << 32) | v;
  asm volatile("st.relaxed.gpu.global.b64 [%0], %1;" ::"l"(p), "l"(w) : "memory");
}
__device__ __forceinline__ uint2 ld_relaxed64v(const void* p) {
  uint2 w;
  asm volatile("ld.relaxed.gpu.global.v2.b32 {%0,%1}, [%2];" : "=r"(w.x), "=r"(w.y) : "l"(p) : "memory");
  return w;
}
__device__ __forceinline__ uint32_t ld_relaxed32(const void* p) {
  uint32_t w;
  asm volatile("ld.relaxed.gpu.global.b32 %0, [%1];" : "=r"(w) : "l"(p) : "memory");
  return w;
}
__device__ __forceinline__ uint4 ld_relaxed128(const void* p) {
  uint4 w;
  asm volatile("ld.relaxed.gpu.global.v4.b32 {%0,%1,%2,%3}, [%4];"
               : "=r"(w.x), "=r"(w.y), "=r"(w.z), "=r"(w.w) : "l"(p) : "memory");
  return w;
}
__device__ __forceinline__ void st_relaxed32(void* p, uint32_t v) {
  asm volatile("st.relaxed.gpu.global.b32 [%0], %1;" ::"l"(p), "r"(v) : "memory");
}
__device__ __forceinline__ void st_relaxed64v(void* p, uint32_t a, uint32_t b) {
  asm volatile("st.relaxed.gpu.global.v2.b32 [%0], {%1,%2};" ::"l"(p), "r"(a), "r"(b) : "memory");
}
__device__ __forceinline__ uint32_t tag2(float v, uint32_t tag) { return (__float_as_uint(v) & ~3u) | (tag & 3u); }
__device__ __forceinline__ bool ok2(uint32_t w, uint32_t tag) { return ((w ^ tag) & 3u) == 0u; }
__device__ __forceinline__ bool ok2(const uint4& w, uint32_t tag) {
  return (((w.x ^ tag) | (w.y ^ tag) | (w.z ^ tag) | (w.w ^ tag)) & 3u) == 0u;
}
__device__ __forceinline__ bool ok16(const uint4& w, uint32_t tag) {
  return (((w.x ^ tag) | (w.y ^ tag) | (w.z ^ tag) | (w.w ^ tag)) & 0xffffu) == 0u;
}
__device__ __forceinline__ void spin_check(unsigned& n) {
  if (++n > SPIN_LIMIT) __trap();
}
__device__ __forceinline__ void add4(float (&a)[4], const uint4& w) {
  a[0] += __uint_as_float(w.x); a[1] += __uint_as_float(w.y); a[2] += __uint_as_float(w.z); a[3] += __uint_as_float(w.w);
}
__device__ __forceinline__ unsigned draw_tickets(unsigned n) {
  unsigned r, lane;
  asm volatile("mov.u32 %0, %%laneid;" : "=r"(lane));
  asm volatile("atom.relaxed.gpu.global.add.u32 %0, [%1], %2;" : "=r"(r) : "l"(&g_ticket + lane), "r"(n) : "memory");
  return r;
}
#define DBG_T(i) do { } while (0)

__device__ __noinline__ float gemv32(uint32_t wbase, const uint32_t* v32, int nks, int wi, int nw, float* red,
                                     int barid) {
  const int lane = threadIdx.x & 31, g = lane >> 2, t = lane & 3;
  float c0[4] = {0.f, 0.f, 0.f, 0.f}, c1[4] = {0.f, 0.f, 0.f, 0.f};
  const int rl = (lane & 7) + ((lane >> 4) << 3), ch = (lane >> 3) & 1;
  const uint32_t sw = (rl >> 1) & 3;
  const uint32_t a0 = wbase + rl * 64 + ((ch ^ sw) << 4), a1 = wbase + rl * 64 + (((2 + ch) ^ sw) << 4);
#pragma unroll 3
  for (int ks = wi; ks < nks; ks += nw) {
    uint32_t r0, r1, r2, r3, r4, r5, r6, r7;
    ldsm4t(a0 + ks * 1024, r0, r1, r2, r3);
    ldsm4t(a1 + ks * 1024, r4, r5, r6, r7);
    const uint32_t b0 = v32[ks * 8 + t], b1 = v32[ks * 8 + 4 + t];
    mma16816(c0, r0, r1, r2, r3, b0, b1);
    mma16816(c1, r4, r5, r6, r7, b0, b1);
  }
  if (t < 2) {
    red[wi * 32 + t * 8 + g] = t ? c0[2] : c0[0];
    red[wi * 32 + 16 + t * 8 + g] = t ? c1[2] : c1[0];
  }
  named_sync(barid, nw * 32);
  float r = 0.f;
  if (wi == 0)
    for (int w = 0; w < nw; w++) r += red[w * 32 + lane];
  return r;
}

__device__ __noinline__ void gemv576(uint32_t wbase, const uint32_t* v32, bool k40, int wi, int nw, float* out,
                                     uint32_t tag) {
  const int lane = threadIdx.x & 31, g = lane >> 2, t = lane & 3;
  const uint32_t b0 = v32[t], b1 = v32[4 + t], b2 = v32[8 + t], b3 = v32[12 + t];
  const uint32_t b4 = k40 ? v32[16 + t] : 0u;
  const uint32_t ra = wbase + ((lane & 7) + ((lane >> 4) << 3)) * ROWP + ((lane >> 3) & 1) * 16;
  const uint32_t rb = wbase + (32 + (lane & 7)) * ROWP + ((lane >> 3) & 1) * 16;
#pragma unroll 1
  for (int m0 = wi; m0 < 36; m0 += 3 * nw) {
    uint32_t r[3][10];
    float c[3][4];
#pragma unroll
    for (int j = 0; j < 3; j++) {
      const int mt = min(m0 + j * nw, 35);
      ldsm4t(ra + mt * 32, r[j][0], r[j][1], r[j][2], r[j][3]);
      ldsm4t(ra + 16 * ROWP + mt * 32, r[j][4], r[j][5], r[j][6], r[j][7]);
      r[j][8] = r[j][9] = 0u;
      if (k40) ldsm2t(rb + mt * 32, r[j][8], r[j][9]);
    }
#pragma unroll
    for (int j = 0; j < 3; j++) {
      c[j][0] = c[j][1] = c[j][2] = c[j][3] = 0.f;
      mma16816(c[j], r[j][0], r[j][1], r[j][2], r[j][3], b0, b1);
    }
#pragma unroll
    for (int j = 0; j < 3; j++) mma16816(c[j], r[j][4], r[j][5], r[j][6], r[j][7], b2, b3);
#pragma unroll
    for (int j = 0; j < 3; j++) mma1688(c[j], r[j][8], r[j][9], b4);
#pragma unroll
    for (int j = 0; j < 3; j++) {
      const int mt = m0 + j * nw;
      if (t < 2 && mt < 36) st_relaxed32(out + mt * 16 + t * 8 + g, tag2(t ? c[j][2] : c[j][0], tag));
    }
  }
}

struct LnStats { float mb, den; };
__device__ __forceinline__ LnStats ln_stats(const float (&xa)[4], const float (&xb)[4], float* red, int warp, int lane) {
  float s = (xa[0] + xa[1]) + (xa[2] + xa[3]) + (xb[0] + xb[1]) + (xb[2] + xb[3]);
#pragma unroll
  for (int of = 16; of > 0; of >>= 1) s += __shfl_xor_sync(0xffffffffu, s, of);
  if (lane == 0) red[warp] = s;
  named_sync(3, 128);
  const float mean = (red[0] + red[1] + red[2] + red[3]) * (1.f / D);
  const bool two = warp == 0 && lane < 16;
  float v = 0.f;
#pragma unroll
  for (int j = 0; j < 4; j++) {
    const float d = xa[j] - mean, e = two ? xb[j] - mean : 0.f;
    v += d * d + e * e;
  }
#pragma unroll
  for (int of = 16; of > 0; of >>= 1) v += __shfl_xor_sync(0xffffffffu, v, of);
  if (lane == 0) red[4 + warp] = v;
  named_sync(3, 128);
  const float var = (red[4] + red[5] + red[6] + red[7]) * (1.f / D);
  LnStats r;
  r.mb = bfr(mean);
  r.den = bfr(fsqrt(bfr(bfr(var) + 1e-5f)));
  return r;
}
__device__ __forceinline__ uint2 ln_apply(const float (&x)[4], const LnStats& st, const uint4& scw, const uint4& shw) {
  const float sc[4] = {bf_hi(scw.x), bf_hi(scw.y), bf_hi(scw.z), bf_hi(scw.w)};
  const float sh[4] = {bf_hi(shw.x), bf_hi(shw.y), bf_hi(shw.z), bf_hi(shw.w)};
  float h[4];
#pragma unroll
  for (int j = 0; j < 4; j++) {
    const float n = bfr(__fdividef(bfr(x[j] - st.mb), st.den));
    h[j] = bfr(n * bfr(1.f + sc[j])) + sh[j];
  }
  return make_uint2(pack_bf2(h[0], h[1]), pack_bf2(h[2], h[3]));
}

struct Params {
  const __nv_bfloat16* x;
  const __nv_bfloat16* c;
  const __nv_bfloat16* wo;
  const __nv_bfloat16* wdown;
  __nv_bfloat16* out;
};

enum { B_FULL = 0, B_EMPTY = S, B_MODA = 2 * S, B_WQ, B_MODB, B_WO, B_UP = B_WO + 2, B_GATE = B_UP + 3,
       B_DOWN = B_GATE + 3, B_Q0 = B_DOWN + 4, B_QALL, B_W1FREE2, B_MFULL0, B_MFULL1, B_MFREE0, B_MFREE1, B_UPFREE,
       B_JOBDONE, B_W1FREE, B_COUNT };
static_assert(B_COUNT * 8 <= 336, "barrier area");

__global__ void __launch_bounds__(288, 1)
fused_kernel(const __grid_constant__ CUtensorMap mapK, const __grid_constant__ CUtensorMap mapV,
             const __grid_constant__ CUtensorMap mapModA, const __grid_constant__ CUtensorMap mapMod,
             const __grid_constant__ CUtensorMap mapWq,
             const __grid_constant__ CUtensorMap mapGate, const __grid_constant__ CUtensorMap mapUp,
             const Params p) {
  extern __shared__ __align__(1024) unsigned char sp[];
  const uint32_t sb = smem_u32(sp);
  if (sb & 1023u) __trap();
  const int tid = threadIdx.x, warp = tid >> 5, lane = tid & 31;
  const int cta = blockIdx.x, G = gridDim.x;
  const uint32_t bar0 = sb + OFF_BAR;
  auto BAR = [&](int i) { return bar0 + 8u * i; };
  volatile int* s_tile = reinterpret_cast<volatile int*>(sp + OFF_BAR + 336);
  volatile int* s_minfo = reinterpret_cast<volatile int*>(sp + OFF_BAR + 360);

  if (warp == 8) {
    const uint64_t pol = stream_policy();
    if (lane == 0) {
      DBG_T(0);
      prefetch_map(&mapModA);
      prefetch_map(&mapWq);
      prefetch_map(&mapK);
      prefetch_map(&mapV);
      for (int i = 0; i < S; i++) { mbar_init(BAR(B_FULL + i), 1); mbar_init(BAR(B_EMPTY + i), 4); }
      for (int i = B_MODA; i < B_Q0; i++) mbar_init(BAR(i), 1);
      for (int i = B_Q0; i < B_W1FREE; i++) mbar_init(BAR(i), 4);
      mbar_init(BAR(B_W1FREE), 8);
      asm volatile("fence.proxy.async.shared::cta;" ::: "memory");
      if (cta < NMODA) {
        mbar_expect_tx(BAR(B_MODA), 576 * 32);
        for (int i = 0; i < 3; i++) tma2d(sb + OFF_UP + i * 6144, &mapModA, cta * 16, i * 192, BAR(B_MODA), pol);
      }
      DBG_T(22);
    }
    __syncthreads();
    if (lane == 0) {
      auto load_tile = [&](int stage, int tile) {
        s_tile[stage] = tile;
        mbar_expect_tx(BAR(B_FULL + stage), STAGE_BYTES);
        tma3d(sb + OFF_RING + stage * STAGE_BYTES, &mapK, 0, tile * R, 0, BAR(B_FULL + stage), pol);
        tma3d(sb + OFF_RING + stage * STAGE_BYTES + 8192, &mapV, 0, tile * R, 0, BAR(B_FULL + stage), pol);
      };
      if (cta < NJOB) {
        mbar_expect_tx(BAR(B_WQ), 576 * 64);
        for (int i = 0; i < 3; i++) tma2d(sb + OFF_W1 + i * 12288, &mapWq, cta * 32, i * 192, BAR(B_WQ), pol);
      }
      const unsigned ntd = NT - S * G;
      unsigned ncnt = TBATCH, nbase = draw_tickets(TBATCH);
      const int ustart = 72 * (cta >> 1) + 40 * (cta & 1);
      const bool job = cta < NJOB;
      auto head_chunk = [&](int i) {
        if (i < S) {
          load_tile(i, i * G + cta);
        } else if (job) {
          if (i < S + 2) {
            const int j = i - S;
            mbar_expect_tx(BAR(B_WO + j), 16 * 1152);
            for (int r = 16 * j; r < 16 * j + 16; r++)
              bulk_load(sb + OFF_W2 + r * ROWP, p.wo + (size_t)(cta * 32 + r) * D, 1152, BAR(B_WO + j), pol);
          } else {
            const int j = i - S - 2;
            if (j == 0 && cta < NMODA) mbar_wait(BAR(B_UPFREE), 0);
            mbar_expect_tx(BAR(B_UP + j), 192 * 80);
            tma2d(sb + OFF_UP + j * 15360, &mapUp, ustart, j * 192, BAR(B_UP + j), pol);
          }
        }
      };
      auto head_bar = [&](int i) { return i < S ? B_FULL + i : B_WO + (i - S); };
      if (cta < NMODA) mbar_wait(BAR(B_MODA), 0);
      DBG_T(24);
      prefetch_map(&mapUp);
#pragma unroll 1
      for (int i = 0; i < S + 5; i++) {
        if (i == HW - 1 && job) { mbar_wait(BAR(B_WQ), 0); DBG_T(25); }
        if (i >= HW && (job || i - HW < S)) mbar_wait(BAR(head_bar(i - HW)), 0);
        head_chunk(i);
      }
      prefetch_map(&mapMod);
      prefetch_map(&mapGate);
      if (cta < NMODB) {
        mbar_wait(BAR(B_W1FREE), 0);
        mbar_expect_tx(BAR(B_MODB), 576 * 64);
        for (int i = 0; i < 3; i++) tma2d(sb + OFF_W1 + i * 12288, &mapMod, 2 * D + cta * 32, i * 192, BAR(B_MODB), pol);
      }
      int stage = 0;
      uint32_t ph = 0;
      DBG_T(26);
      while (true) {
        const unsigned base = nbase, cnt = ncnt;
        if (base >= ntd) break;
        ncnt = (base + TEND * G < ntd) ? TBATCH : 1u;
        nbase = draw_tickets(ncnt);
#pragma unroll 1
        for (unsigned d = base; d < base + cnt && d < ntd; d++) {
          mbar_wait(BAR(B_EMPTY + stage), ph);
          load_tile(stage, S * G + (int)d);
          if (++stage == S) { stage = 0; ph ^= 1; }
        }
      }
      DBG_T(1);
      mbar_wait(BAR(B_EMPTY + stage), ph);
      s_tile[stage] = -1;
      mbar_arrive(BAR(B_FULL + stage));
      if (job) {
        auto gate_chunk = [&](int j) {
          mbar_expect_tx(BAR(B_GATE + j), 192 * 80);
          tma2d(sb + OFF_W1 + j * 15360, &mapGate, ustart, j * 192, BAR(B_GATE + j), pol);
        };
        const int nr = (cta & 1) ? 8 : 10;
        auto down_chunk = [&](int j) {
          mbar_expect_tx(BAR(B_DOWN + j), nr * 1152);
          for (int r = nr * j; r < nr * j + nr; r++)
            bulk_load(sb + OFF_RING + r * ROWP, p.wdown + (size_t)(ustart + r) * D, 1152, BAR(B_DOWN + j), pol);
        };
        mbar_wait(BAR(B_W1FREE2), 0);
        gate_chunk(0);
        gate_chunk(1);
        mbar_wait(BAR(B_GATE), 0);
        gate_chunk(2);
        mbar_wait(BAR(B_EMPTY + stage), ph ^ 1u);
        down_chunk(0);
        down_chunk(1);
        mbar_wait(BAR(B_DOWN), 0);
        down_chunk(2);
        mbar_wait(BAR(B_DOWN + 1), 0);
        down_chunk(3);
      }
      DBG_T(2);
    }
    return;
  }

  uint32_t* vec32 = reinterpret_cast<uint32_t*>(sp + OFF_VEC);
  uint32_t* sc32 = reinterpret_cast<uint32_t*>(sp + OFF_SC);
  float* red = reinterpret_cast<float*>(sp + OFF_RED);
  __nv_bfloat16* smallv = reinterpret_cast<__nv_bfloat16*>(sp + OFF_SM);
  float* mbuf = reinterpret_cast<float*>(sp + OFF_MB);
  const unsigned tag = *(volatile unsigned*)&g_epoch + 1u;
  const bool two = tid < 16;
  const int c0 = 4 * tid, c1 = 512 + 4 * tid;

  if (warp < 4) {
    float xa[4], xb[4] = {0.f, 0.f, 0.f, 0.f};
    {
      const uint2 a = *reinterpret_cast<const uint2*>(p.x + c0);
      xa[0] = bf_lo(a.x); xa[1] = bf_hi(a.x); xa[2] = bf_lo(a.y); xa[3] = bf_hi(a.y);
      if (two) {
        const uint2 b = *reinterpret_cast<const uint2*>(p.x + c1);
        xb[0] = bf_lo(b.x); xb[1] = bf_hi(b.x); xb[2] = bf_lo(b.y); xb[3] = bf_hi(b.y);
      }
    }
    __syncthreads();
    const LnStats st = ln_stats(xa, xb, red + 256, warp, lane);
    if (tid == 0) DBG_T(3);
    {
      const unsigned* ma = g_modA + (cta & (NREP - 1)) * 2 * D;
      uint4 w[4];
      unsigned n = 0;
      while (true) {
        w[0] = ld_relaxed128(ma + c0);
        w[1] = ld_relaxed128(ma + D + c0);
        bool ok = ok16(w[0], tag) && ok16(w[1], tag);
        if (two) {
          w[2] = ld_relaxed128(ma + c1);
          w[3] = ld_relaxed128(ma + D + c1);
          ok = ok && ok16(w[2], tag) && ok16(w[3], tag);
        }
        if (ok) break;
        spin_check(n);
      }
      if (tid == 0) DBG_T(23);
      *reinterpret_cast<uint2*>(vec32 + 2 * tid) = ln_apply(xa, st, w[1], w[0]);
      if (two) *reinterpret_cast<uint2*>(vec32 + 256 + 2 * tid) = ln_apply(xb, st, w[3], w[2]);
    }
  } else {
    const int st = tid - 128;
    if (st < 72) {
      const uint4 a = *reinterpret_cast<const uint4*>(p.c + st * 8);
      uint4 r;
      r.x = pack_bf2(silu(bf_lo(a.x)), silu(bf_hi(a.x))); r.y = pack_bf2(silu(bf_lo(a.y)), silu(bf_hi(a.y)));
      r.z = pack_bf2(silu(bf_lo(a.z)), silu(bf_hi(a.z))); r.w = pack_bf2(silu(bf_lo(a.w)), silu(bf_hi(a.w)));
      *reinterpret_cast<uint4*>(sc32 + st * 4) = r;
    }
    __syncthreads();
    if (cta < NMODA) {
      named_sync(2, 128);
      if (st == 0) DBG_T(20);
      mbar_wait(BAR(B_MODA), 0);
      if (st == 0) DBG_T(21);
      const int g = lane >> 2, t = lane & 3, sw = warp - 4;
      const uint32_t wa = sb + OFF_UP + ((lane & 7) + ((lane >> 4) << 3)) * 32 + ((lane >> 3) & 1) * 16;
      float c[3][4];
#pragma unroll
      for (int j = 0; j < 3; j++) { c[j][0] = c[j][1] = c[j][2] = c[j][3] = 0.f; }
#pragma unroll 1
      for (int k0 = sw; k0 < 36; k0 += 12) {
        uint32_t r[3][4], b[3][2];
#pragma unroll
        for (int j = 0; j < 3; j++) {
          ldsm4t(wa + (k0 + 4 * j) * 512, r[j][0], r[j][1], r[j][2], r[j][3]);
          b[j][0] = sc32[(k0 + 4 * j) * 8 + t]; b[j][1] = sc32[(k0 + 4 * j) * 8 + 4 + t];
        }
#pragma unroll
        for (int j = 0; j < 3; j++) mma16816(c[j], r[j][0], r[j][1], r[j][2], r[j][3], b[j][0], b[j][1]);
      }
      if (t < 2) red[sw * 16 + t * 8 + g] = t ? c[0][2] + c[1][2] + c[2][2] : c[0][0] + c[1][0] + c[2][0];
      __syncwarp();
      if (lane == 0) mbar_arrive(BAR(B_UPFREE));
      named_sync(2, 128);
      const int col = st & 15;
      const float r = (red[col] + red[16 + col]) + (red[32 + col] + red[48 + col]);
      st_relaxed32(&g_modA[(st >> 4) * 2 * D + cta * 16 + col], __float_as_uint(bfr(r)) | (tag & 0xffffu));
      if (st == 0) DBG_T(16);
    }
  }
  named_sync(1, 256);
  if (tid == 0) DBG_T(4);
  if (cta < NJOB) {
    mbar_wait(BAR(B_WQ), 0);
    if (tid == 0) DBG_T(17);
    const float r = gemv32(sb + OFF_W1, vec32, 36, warp, 8, red, 1);
    if (warp == 0) {
      const uint32_t pk = pack_bf2(r, __shfl_down_sync(0xffffffffu, r, 1));
      const uint32_t w = __shfl_sync(0xffffffffu, pk, 2 * (lane & 15));
      if (cta < NQ0) {
#pragma unroll
        for (int i = 0; i < NREP / 2; i++) st_ll(&g_q0[((lane >> 4) + 2 * i) * NQ0 * 16 + cta * 16 + (lane & 15)], w, tag);
      } else if (lane < 16) {
        st_ll(&g_q[cta * 16 + lane], w, tag);
      }
    }
    if (tid == 0) DBG_T(18);
  }
  __syncwarp();
  if (lane == 0) mbar_arrive(BAR(B_W1FREE));

  if (warp < 4) {
    const int g = lane >> 2, t = lane & 3;
    const uint32_t* qs32 = reinterpret_cast<const uint32_t*>(sp + OFF_QS);
    uint32_t qf[16];
    float o[8][4];
    float m = -INFINITY, l = 0.f;
    int cur = -1, nflush = 0;
    const int key = warp * 8 + (lane & 7);
    uint32_t koff[4];
#pragma unroll
    for (int u = 0; u < 4; u++) {
      const int chunk = 4 * u + (lane >> 3);
      koff[u] = (chunk >> 3) * 4096 + key * 128 + (((chunk & 7) ^ (key & 7)) << 4);
    }
#pragma unroll
    for (int i = 0; i < 8; i++) { o[i][0] = o[i][1] = o[i][2] = o[i][3] = 0.f; }
#pragma unroll
    for (int i = 0; i < 16; i++) qf[i] = 0u;

    int stage = 0;
    uint32_t ph = 0;
    while (true) {
      mbar_wait(BAR(B_FULL + stage), ph);
      const int tile = s_tile[stage];
      const int head = (tile < 0) ? HKV : (tile >> TPH_SHIFT);
      if (head != cur) {
        if (cur >= 0 || head > 0) {
          const int pb = nflush & 1;
          if (nflush >= 2) mbar_wait(BAR(B_MFREE0 + pb), ((nflush >> 1) - 1) & 1);
          float* mb = mbuf + pb * MB_FLOATS + warp * 264;
          float lr = l;
          lr += __shfl_xor_sync(0xffffffffu, lr, 1);
          lr += __shfl_xor_sync(0xffffffffu, lr, 2);
          if (t == 0) {
#pragma unroll
            for (int i = 0; i < 8; i++) {
              mb[16 * i + g] = o[i][0];
              mb[132 + 16 * i + g] = o[i][1];
              mb[16 * i + 8 + g] = o[i][2];
              mb[132 + 16 * i + 8 + g] = o[i][3];
            }
            if (g < 2) { mb[g * 132 + 128] = m * LOG2E; mb[g * 132 + 129] = lr; }
          }
          if (warp == 0 && lane == 0) { s_minfo[pb * 2] = cur; s_minfo[pb * 2 + 1] = head; }
          __syncwarp();
          if (lane == 0) mbar_arrive(BAR(B_MFULL0 + pb));
          nflush++;
        }
        if (tile < 0) break;
        if (cur < 0 && tid == 0) DBG_T(13);
        cur = head;
        m = -INFINITY; l = 0.f;
#pragma unroll
        for (int i = 0; i < 8; i++) { o[i][0] = o[i][1] = o[i][2] = o[i][3] = 0.f; }
        mbar_wait(BAR(head < 2 ? B_Q0 : B_QALL), 0);
        if (g < 2) {
          const uint32_t* qh = qs32 + (2 * head + g) * 64;
#pragma unroll
          for (int s = 0; s < 8; s++) { qf[2 * s] = qh[8 * s + t]; qf[2 * s + 1] = qh[8 * s + 4 + t]; }
        }
        if (head == 0 && tid == 0) DBG_T(5);
      }
      const uint32_t kb = sb + OFF_RING + stage * STAGE_BYTES;
      uint32_t kr[16], vr[16];
#pragma unroll
      for (int u = 0; u < 4; u++) ldsm4(kb + koff[u], kr[4 * u], kr[4 * u + 1], kr[4 * u + 2], kr[4 * u + 3]);
#pragma unroll
      for (int u = 0; u < 4; u++) ldsm4t(kb + 8192 + koff[u], vr[4 * u], vr[4 * u + 1], vr[4 * u + 2], vr[4 * u + 3]);
      float sa[4] = {0.f, 0.f, 0.f, 0.f}, sbb[4] = {0.f, 0.f, 0.f, 0.f};
#pragma unroll
      for (int u = 0; u < 4; u++) {
        mma16816(sa, qf[4 * u], 0u, qf[4 * u + 1], 0u, kr[4 * u], kr[4 * u + 1]);
        mma16816(sbb, qf[4 * u + 2], 0u, qf[4 * u + 3], 0u, kr[4 * u + 2], kr[4 * u + 3]);
      }
      const uint32_t sraw = pack_bf2(sa[0] + sbb[0], sa[1] + sbb[1]);
      const uint32_t ssc = pack_bf2(bf_lo(sraw) * SCALE, bf_hi(sraw) * SCALE);
      const float s0 = bf_lo(ssc), s1 = bf_hi(ssc);
      float tm = fmaxf(s0, s1);
      tm = fmaxf(tm, __shfl_xor_sync(0xffffffffu, tm, 1));
      tm = fmaxf(tm, __shfl_xor_sync(0xffffffffu, tm, 2));
      const float mn = fmaxf(m, tm);
      if (__any_sync(0xffffffffu, g < 2 && mn > m)) {
        const float alpha = ex2((m - mn) * LOG2E);
        l *= alpha;
        const float a0 = __shfl_sync(0xffffffffu, alpha, 0), a1 = __shfl_sync(0xffffffffu, alpha, 4);
#pragma unroll
        for (int i = 0; i < 8; i++) { o[i][0] *= a0; o[i][1] *= a1; o[i][2] *= a0; o[i][3] *= a1; }
        m = mn;
      }
      float p0 = ex2((s0 - m) * LOG2E), p1 = ex2((s1 - m) * LOG2E);
      if (g >= 2) { p0 = 0.f; p1 = 0.f; }
      l += p0 + p1;
      const uint32_t pk = pack_bf2(p0, p1);
#pragma unroll
      for (int i = 0; i < 8; i++) mma1688(o[i], vr[2 * i], vr[2 * i + 1], pk);
      __syncwarp();
      if (lane == 0) mbar_arrive(BAR(B_EMPTY + stage));
      if (++stage == S) { stage = 0; ph ^= 1; }
    }
    __syncwarp();
    if (lane == 0) mbar_arrive(BAR(B_EMPTY + stage));
    if (tid == 0) DBG_T(6);
    if (cta >= NJOB) return;

    uint4 ga0, sb0, cb0, ga1, sb1, cb1;
    uint2 xw0, xw1 = make_uint2(0u, 0u);
    float y0[4] = {0.f, 0.f, 0.f, 0.f}, y1[4] = {0.f, 0.f, 0.f, 0.f};
    unsigned n = 0;
    xw0 = *reinterpret_cast<const uint2*>(p.x + c0);
    if (two) xw1 = *reinterpret_cast<const uint2*>(p.x + c1);
    ga0 = ld_relaxed128(&g_modB[c0]); sb0 = ld_relaxed128(&g_modB[D + c0]); cb0 = ld_relaxed128(&g_modB[2 * D + c0]);
    ga1 = ga0; sb1 = sb0; cb1 = cb0;
    if (two) { ga1 = ld_relaxed128(&g_modB[c1]); sb1 = ld_relaxed128(&g_modB[D + c1]); cb1 = ld_relaxed128(&g_modB[2 * D + c1]); }
    if (cta < NRED) {
      const int j = tid >> 1;
      const float* yp = g_yp + (size_t)j * D + cta * 8 + (tid & 1) * 4;
      uint4 wa, wb = make_uint4(tag & 3u, tag & 3u, tag & 3u, tag & 3u);
      while (true) {
        wa = ld_relaxed128(yp);
        if (j + 64 < NEARLY) wb = ld_relaxed128(yp + 64 * D);
        if (ok2(wa, tag) && ok2(wb, tag)) break;
        spin_check(n);
      }
      float f[4] = {0.f, 0.f, 0.f, 0.f};
      add4(f, wa);
      add4(f, wb);
#pragma unroll
      for (int o = 2; o <= 16; o <<= 1)
#pragma unroll
        for (int i = 0; i < 4; i++) f[i] += __shfl_xor_sync(0xffffffffu, f[i], o);
      float* rp = red + 264;
      if (lane < 2) {
#pragma unroll
        for (int i = 0; i < 4; i++) rp[warp * 8 + lane * 4 + i] = f[i];
      }
      named_sync(3, 128);
      if (tid < 8 * NREP) {
        const int i = tid & 7;
        st_relaxed32(&g_ye[(tid >> 3) * D + cta * 8 + i], tag2((rp[i] + rp[8 + i]) + (rp[16 + i] + rp[24 + i]), tag));
      }
      if (tid == 0) DBG_T(19);
    }
    while (!(ok2(ga0, tag) && ok2(sb0, tag) && ok2(cb0, tag) && ok2(ga1, tag) && ok2(sb1, tag) && ok2(cb1, tag))) {
      spin_check(n);
      ga0 = ld_relaxed128(&g_modB[c0]); sb0 = ld_relaxed128(&g_modB[D + c0]); cb0 = ld_relaxed128(&g_modB[2 * D + c0]);
      if (two) { ga1 = ld_relaxed128(&g_modB[c1]); sb1 = ld_relaxed128(&g_modB[D + c1]); cb1 = ld_relaxed128(&g_modB[2 * D + c1]); }
    }
    if (cta >= NEARLY) {
      mbar_wait(BAR(B_JOBDONE), 0);
    } else {
      const unsigned* fl = g_flag + (cta & (NREP - 1)) * 32 + (lane & 7);
      while (!__all_sync(0xffffffffu, ld_relaxed32(fl) == tag)) spin_check(n);
    }
    if (tid == 0) DBG_T(14);
    {
      const float* ye = g_ye + (cta & (NREP - 1)) * D;
      uint4 w[9], w2[9];
      while (true) {
        bool ok = true;
        w[8] = ld_relaxed128(ye + c0);
#pragma unroll
        for (int j = 0; j < 8; j++) w[j] = ld_relaxed128(&g_yp[(NEARLY + j) * D + c0]);
        if (two) {
          w2[8] = ld_relaxed128(ye + c1);
#pragma unroll
          for (int j = 0; j < 8; j++) w2[j] = ld_relaxed128(&g_yp[(NEARLY + j) * D + c1]);
#pragma unroll
          for (int j = 0; j < 9; j++) ok = ok && ok2(w2[j], tag);
        }
#pragma unroll
        for (int j = 0; j < 9; j++) ok = ok && ok2(w[j], tag);
        if (ok) break;
        spin_check(n);
      }
#pragma unroll
      for (int j = 0; j < 9; j++) add4(y0, w[j]);
      if (two) {
#pragma unroll
        for (int j = 0; j < 9; j++) add4(y1, w2[j]);
      }
    }
    if (tid == 0) DBG_T(8);
    float xa[4], xb[4] = {0.f, 0.f, 0.f, 0.f};
    xa[0] = bfr(bf_lo(xw0.x) + bfr(bf_hi(ga0.x) * bfr(y0[0])));
    xa[1] = bfr(bf_hi(xw0.x) + bfr(bf_hi(ga0.y) * bfr(y0[1])));
    xa[2] = bfr(bf_lo(xw0.y) + bfr(bf_hi(ga0.z) * bfr(y0[2])));
    xa[3] = bfr(bf_hi(xw0.y) + bfr(bf_hi(ga0.w) * bfr(y0[3])));
    if (two) {
      xb[0] = bfr(bf_lo(xw1.x) + bfr(bf_hi(ga1.x) * bfr(y1[0])));
      xb[1] = bfr(bf_hi(xw1.x) + bfr(bf_hi(ga1.y) * bfr(y1[1])));
      xb[2] = bfr(bf_lo(xw1.y) + bfr(bf_hi(ga1.z) * bfr(y1[2])));
      xb[3] = bfr(bf_hi(xw1.y) + bfr(bf_hi(ga1.w) * bfr(y1[3])));
    }
    const LnStats st = ln_stats(xa, xb, red + 256, warp, lane);
    uint32_t* x1s = reinterpret_cast<uint32_t*>(sp + OFF_QS);
    *reinterpret_cast<uint2*>(vec32 + 2 * tid) = ln_apply(xa, st, cb0, sb0);
    *reinterpret_cast<uint2*>(x1s + 2 * tid) = make_uint2(pack_bf2(xa[0], xa[1]), pack_bf2(xa[2], xa[3]));
    if (two) {
      *reinterpret_cast<uint2*>(vec32 + 256 + 2 * tid) = ln_apply(xb, st, cb1, sb1);
      *reinterpret_cast<uint2*>(x1s + 256 + 2 * tid) = make_uint2(pack_bf2(xb[0], xb[1]), pack_bf2(xb[2], xb[3]));
    }
  } else {
    const int st = tid - 128, sw = warp - 4;
    {
      uint32_t* qs32 = reinterpret_cast<uint32_t*>(sp + OFF_QS);
      unsigned n = 0;
      {
        const unsigned long long* q0 = g_q0 + (cta & (NREP - 1)) * NQ0 * 16 + st * 2;
        uint4 w = ld_relaxed128(q0);
        while (w.y != tag || w.w != tag) { spin_check(n); w = ld_relaxed128(q0); }
        *reinterpret_cast<uint2*>(qs32 + st * 2) = make_uint2(w.x, w.z);
        __syncwarp();
        if (lane == 0) mbar_arrive(BAR(B_Q0));
      }
      while (true) {
        uint4 w[7];
        bool ok = true;
#pragma unroll
        for (int k = 0; k < 7; k++) w[k] = ld_relaxed128(&g_q[(st + 128 * (k + 1)) * 2]);
#pragma unroll
        for (int k = 0; k < 7; k++) {
          ok = ok && w[k].y == tag && w[k].w == tag;
          *reinterpret_cast<uint2*>(qs32 + (st + 128 * (k + 1)) * 2) = make_uint2(w[k].x, w[k].z);
        }
        if (ok) break;
        spin_check(n);
        __nanosleep(200);
      }
      __syncwarp();
      if (lane == 0) mbar_arrive(BAR(B_QALL));
    }
    if (cta < NMODB) {
      mbar_wait(BAR(B_MODB), 0);
      const float r = gemv32(sb + OFF_W1, sc32, 36, sw, 4, red, 2);
      if (st < 32) st_relaxed32(&g_modB[cta * 32 + st], tag2(bfr(r), tag));
    }
    __syncwarp();
    if (lane == 0) mbar_arrive(BAR(B_W1FREE2));
    const int jobhead = (cta < NJOB) ? (cta >> 3) : -1;
    int nflush = 0;
    while (true) {
      const int pb = nflush & 1;
      mbar_wait(BAR(B_MFULL0 + pb), (nflush >> 1) & 1);
      const int from = s_minfo[pb * 2], to = s_minfo[pb * 2 + 1];
      if (from >= 0) {
        const float* mb = mbuf + pb * MB_FLOATS;
#pragma unroll
        for (int e = 0; e < 2; e++) {
          float mw[4], M = -INFINITY;
#pragma unroll
          for (int w = 0; w < 4; w++) { mw[w] = mb[w * 264 + e * 132 + 128]; M = fmaxf(M, mw[w]); }
          float acc = 0.f, L = 0.f;
#pragma unroll
          for (int w = 0; w < 4; w++) {
            const float f = ex2(mw[w] - M);
            acc += f * mb[w * 264 + e * 132 + st];
            L += f * mb[w * 264 + e * 132 + 129];
          }
          st_relaxed32(&g_recO[(((from * 2 + e) * 4 + sw) * MAXG + cta) * 32 + lane], tag2(acc, tag));
          if (st == 0) st_relaxed64v(&g_recML[((from * 2 + e) * MAXG + cta) * 2], tag2(M, tag), tag2(L, tag));
        }
      }
      for (int h = from + 1; h < to; h++) {
#pragma unroll
        for (int e = 0; e < 2; e++) {
          st_relaxed32(&g_recO[(((h * 2 + e) * 4 + sw) * MAXG + cta) * 32 + lane], tag2(0.f, tag));
          if (st == 0) st_relaxed64v(&g_recML[((h * 2 + e) * MAXG + cta) * 2], tag2(-1e30f, tag), tag2(0.f, tag));
        }
      }
      __syncwarp();
      if (lane == 0) mbar_arrive(BAR(B_MFREE0 + pb));
      nflush++;
      if (jobhead >= 0 && jobhead >= from && jobhead < to) {
        const int he = cta >> 2, rr = cta & 3;
        const int i4 = st & 7, cg = st >> 3;
        const float* rO = g_recO + (size_t)(he * 4 + rr) * MAXG * 32 + i4 * 4;
        const float* rML = g_recML + (size_t)he * MAXG * 2;
        uint4 ov[9];
        uint2 ml[9];
        {
          unsigned n = 0;
          while (true) {
            bool ok = true;
#pragma unroll
            for (int k = 0; k < 9; k++) {
              const int c = cg + 16 * k;
              if (c < G) {
                ov[k] = ld_relaxed128(rO + c * 32);
                ml[k] = ld_relaxed64v(rML + c * 2);
              } else {
                ov[k] = make_uint4(tag & 3u, tag & 3u, tag & 3u, tag & 3u);
                ml[k] = make_uint2(tag2(-1e30f, tag), tag & 3u);
              }
            }
#pragma unroll
            for (int k = 0; k < 9; k++) ok = ok && ok2(ov[k], tag) && ok2(ml[k].x, tag) && ok2(ml[k].y, tag);
            if (ok) break;
            spin_check(n);
          }
        }
        if (st == 0) DBG_T(15);
        float M = __uint_as_float(ml[0].x);
#pragma unroll
        for (int k = 1; k < 9; k++) M = fmaxf(M, __uint_as_float(ml[k].x));
        M = fmaxf(M, __shfl_xor_sync(0xffffffffu, M, 8));
        M = fmaxf(M, __shfl_xor_sync(0xffffffffu, M, 16));
        float4 acc = make_float4(0.f, 0.f, 0.f, 0.f);
        float L = 0.f;
#pragma unroll
        for (int k = 0; k < 9; k++) {
          const float f = ex2(__uint_as_float(ml[k].x) - M);
          acc.x += f * __uint_as_float(ov[k].x); acc.y += f * __uint_as_float(ov[k].y);
          acc.z += f * __uint_as_float(ov[k].z); acc.w += f * __uint_as_float(ov[k].w);
          L += f * __uint_as_float(ml[k].y);
        }
#pragma unroll
        for (int o = 8; o <= 16; o <<= 1) {
          acc.x += __shfl_xor_sync(0xffffffffu, acc.x, o); acc.y += __shfl_xor_sync(0xffffffffu, acc.y, o);
          acc.z += __shfl_xor_sync(0xffffffffu, acc.z, o); acc.w += __shfl_xor_sync(0xffffffffu, acc.w, o);
          L += __shfl_xor_sync(0xffffffffu, L, o);
        }
        if (lane < 8) {
          float* rp = red + 64 + sw * 40;
          rp[lane * 4] = acc.x; rp[lane * 4 + 1] = acc.y; rp[lane * 4 + 2] = acc.z; rp[lane * 4 + 3] = acc.w;
          if (lane == 0) { rp[32] = L; rp[33] = M; }
        }
        if (cta == NJOB - 1 && st == 0) *(volatile unsigned*)&g_ticket = 0u;
        named_sync(2, 128);
        if (cta >= NEARLY && st >= 32 && st < 32 + NREP) st_relaxed32(&g_flag[(st - 32) * 32 + cta - NEARLY], tag);
        if (st < 32) {
          const float* rp = red + 64;
          const float MM = fmaxf(fmaxf(rp[33], rp[73]), fmaxf(rp[113], rp[153]));
          const float f0 = ex2(rp[33] - MM), f1 = ex2(rp[73] - MM), f2 = ex2(rp[113] - MM), f3 = ex2(rp[153] - MM);
          const float num = f0 * rp[st] + f1 * rp[40 + st] + f2 * rp[80 + st] + f3 * rp[120 + st];
          const float den = f0 * rp[32] + f1 * rp[72] + f2 * rp[112] + f3 * rp[152];
          smallv[st] = __float2bfloat16_rn(__fdividef(num, den));
        }
        named_sync(2, 128);
        mbar_wait(BAR(B_WO), 0);
        mbar_wait(BAR(B_WO + 1), 0);
        gemv576(sb + OFF_W2, reinterpret_cast<const uint32_t*>(smallv), false, sw, 4, g_yp + (size_t)cta * D, tag);
        __syncwarp();
        if (lane == 0) mbar_arrive(BAR(B_JOBDONE));
        if (st == 0) DBG_T(7);
      }
      if (to >= HKV) break;
    }
    if (cta >= NJOB) return;
  }
  uint32_t gbw = 0;
  if (cta < NRED && tid >= 128 && tid < 136) {
    unsigned n = 0;
    gbw = ld_relaxed32(&g_modB[3 * D + cta * 8 + tid - 128]);
    while (!ok2(gbw, tag)) { spin_check(n); gbw = ld_relaxed32(&g_modB[3 * D + cta * 8 + tid - 128]); }
  }
  named_sync(1, 256);
  if (tid == 0) DBG_T(9);

  {
    const int g = lane >> 2, t = lane & 3;
    const uint32_t rl = (lane & 7) + ((lane >> 4) << 3), ch = (lane >> 3) & 1;
    const uint32_t wb = sb + OFF_W1 + rl * 80;
    float acc[5][4];
#pragma unroll
    for (int n = 0; n < 5; n++) { acc[n][0] = acc[n][1] = acc[n][2] = acc[n][3] = 0.f; }
#pragma unroll 1
    for (int i = B_UP; i < B_DOWN; i++) mbar_wait(BAR(i), 0);
#pragma unroll 1
    for (int ks = warp; ks < 36; ks += 8) {
      const uint32_t b0 = vec32[ks * 8 + t], b1 = vec32[ks * 8 + 4 + t];
#pragma unroll
      for (int n = 0; n < 5; n++) {
        const uint32_t ci = 2 * n + ch;
        const uint32_t off = (ci >= 5) ? W1_BYTES / 2 + (ci - 5) * 16 : ci * 16;
        uint32_t r0, r1, r2, r3;
        ldsm4t(wb + ks * 1280 + off, r0, r1, r2, r3);
        mma16816(acc[n], r0, r1, r2, r3, b0, b1);
      }
    }
    float* part = mbuf;
    if (t < 2) {
#pragma unroll
      for (int n = 0; n < 5; n++) part[warp * 80 + n * 16 + t * 8 + g] = t ? acc[n][2] : acc[n][0];
    }
    named_sync(1, 256);
    if (tid < 40) {
      float gv = 0.f, uv = 0.f;
#pragma unroll
      for (int w = 0; w < 8; w++) { gv += part[w * 80 + tid]; uv += part[w * 80 + 40 + tid]; }
      smallv[tid] = __float2bfloat16_rn(bfr(silu(bfr(gv))) * bfr(uv));
    }
    named_sync(1, 256);
  }
  if (tid == 0) DBG_T(10);
#pragma unroll 1
  for (int i = B_DOWN; i < B_DOWN + 4; i++) mbar_wait(BAR(i), 0);
  gemv576(sb + OFF_RING, reinterpret_cast<const uint32_t*>(smallv), (cta & 1) == 0, warp, 8, g_z + (size_t)cta * D, tag);
  if (tid == 0) DBG_T(11);
  if (cta < NRED) {
    const int j = tid >> 1, hf = tid & 1;
    const float* zp = g_z + (size_t)j * D + cta * 8 + hf * 4;
    uint4 w = ld_relaxed128(zp);
    unsigned n = 0;
    while (!ok2(w, tag)) { spin_check(n); w = ld_relaxed128(zp); }
    float f0 = __uint_as_float(w.x), f1 = __uint_as_float(w.y), f2 = __uint_as_float(w.z), f3 = __uint_as_float(w.w);
#pragma unroll
    for (int o = 2; o <= 16; o <<= 1) {
      f0 += __shfl_xor_sync(0xffffffffu, f0, o); f1 += __shfl_xor_sync(0xffffffffu, f1, o);
      f2 += __shfl_xor_sync(0xffffffffu, f2, o); f3 += __shfl_xor_sync(0xffffffffu, f3, o);
    }
    float* rp = red + 320;
    if (lane < 2) {
      rp[warp * 8 + lane * 4] = f0; rp[warp * 8 + lane * 4 + 1] = f1;
      rp[warp * 8 + lane * 4 + 2] = f2; rp[warp * 8 + lane * 4 + 3] = f3;
    }
    named_sync(1, 256);
    if (tid >= 128 && tid < 136) {
      const int i = tid - 128;
      float s = 0.f;
#pragma unroll
      for (int w8 = 0; w8 < 8; w8++) s += rp[w8 * 8 + i];
      const int col = cta * 8 + i;
      const float x1 = __bfloat162float(reinterpret_cast<const __nv_bfloat16*>(sp + OFF_QS)[col]);
      p.out[col] = __float2bfloat16_rn(x1 + bfr(bf_hi(gbw) * bfr(s)));
    }
    if (cta == 0 && tid == 0) *(volatile unsigned*)&g_epoch = tag;
  }
  if (tid == 0) DBG_T(12);
}

typedef CUresult (*EncodeFn)(CUtensorMap*, CUtensorMapDataType, cuuint32_t, void*, const cuuint64_t*, const cuuint64_t*,
                             const cuuint32_t*, const cuuint32_t*, CUtensorMapInterleave, CUtensorMapSwizzle,
                             CUtensorMapL2promotion, CUtensorMapFloatOOBfill);

CUtensorMap make_map(EncodeFn enc, const void* base, int rank, const cuuint64_t* dims, const cuuint64_t* strides,
                     const cuuint32_t* box, CUtensorMapSwizzle sw, CUtensorMapL2promotion pr) {
  CUtensorMap m;
  cuuint32_t es[3] = {1, 1, 1};
  enc(&m, CU_TENSOR_MAP_DATA_TYPE_BFLOAT16, rank, const_cast<void*>(base), dims, strides, box, es,
      CU_TENSOR_MAP_INTERLEAVE_NONE, sw, pr, CU_TENSOR_MAP_FLOAT_OOB_FILL_NONE);
  return m;
}

}

extern "C" void kernel_launch(void* const* d_in, const int* in_sizes, int n_in, void* d_out, int out_size) {
  (void)in_sizes; (void)n_in; (void)out_size;
  static EncodeFn enc = nullptr;
  static int nsm = 0;
  if (!enc) {
    void* fn = nullptr;
    cudaDriverEntryPointQueryResult qr;
    cudaGetDriverEntryPoint("cuTensorMapEncodeTiled", &fn, cudaEnableDefault, &qr);
    enc = (EncodeFn)fn;
    int dev = 0;
    cudaGetDevice(&dev);
    cudaDeviceGetAttribute(&nsm, cudaDevAttrMultiProcessorCount, dev);
    cudaFuncSetAttribute(fused_kernel, cudaFuncAttributeMaxDynamicSharedMemorySize, SMEM_BYTES);
  }
  CUtensorMap mK, mV, mModA, mMod, mWq, mG, mU;
  {
    cuuint64_t dims[3] = {64, (cuuint64_t)HKV * SK, 2};
    cuuint64_t str[2] = {256, 128};
    cuuint32_t box[3] = {64, R, 2};
    mK = make_map(enc, d_in[1], 3, dims, str, box, CU_TENSOR_MAP_SWIZZLE_128B, CU_TENSOR_MAP_L2_PROMOTION_L2_256B);
    mV = make_map(enc, d_in[2], 3, dims, str, box, CU_TENSOR_MAP_SWIZZLE_128B, CU_TENSOR_MAP_L2_PROMOTION_L2_256B);
  }
  {
    cuuint64_t dims[2] = {NMOD, D};
    cuuint64_t str[1] = {NMOD * 2};
    cuuint32_t box[2] = {32, 192};
    mMod = make_map(enc, d_in[10], 2, dims, str, box, CU_TENSOR_MAP_SWIZZLE_64B, CU_TENSOR_MAP_L2_PROMOTION_L2_256B);
    cuuint32_t boxa[2] = {16, 192};
    mModA = make_map(enc, d_in[10], 2, dims, str, boxa, CU_TENSOR_MAP_SWIZZLE_NONE, CU_TENSOR_MAP_L2_PROMOTION_L2_256B);
  }
  {
    cuuint64_t dims[2] = {NQ, D};
    cuuint64_t str[1] = {NQ * 2};
    cuuint32_t box[2] = {32, 192};
    mWq = make_map(enc, d_in[3], 2, dims, str, box, CU_TENSOR_MAP_SWIZZLE_64B, CU_TENSOR_MAP_L2_PROMOTION_L2_256B);
  }
  {
    cuuint64_t dims[2] = {FF, D};
    cuuint64_t str[1] = {FF * 2};
    cuuint32_t box[2] = {40, 192};
    mG = make_map(enc, d_in[6], 2, dims, str, box, CU_TENSOR_MAP_SWIZZLE_NONE, CU_TENSOR_MAP_L2_PROMOTION_L2_256B);
    mU = make_map(enc, d_in[7], 2, dims, str, box, CU_TENSOR_MAP_SWIZZLE_NONE, CU_TENSOR_MAP_L2_PROMOTION_L2_256B);
  }
  Params p;
  p.x = (const __nv_bfloat16*)d_in[0];
  p.c = (const __nv_bfloat16*)d_in[9];
  p.wo = (const __nv_bfloat16*)d_in[4];
  p.wdown = (const __nv_bfloat16*)d_in[8];
  p.out = (__nv_bfloat16*)d_out;
  int G = nsm < MAXG ? nsm : MAXG;
  fused_kernel<<<G, 288, SMEM_BYTES, cudaStreamPerThread>>>(mK, mV, mModA, mMod, mWq, mG, mU, p);
}
```

```cpp
#include <cuda_runtime.h>
#include <cuda_bf16.h>
#include <cuda.h>
#include <stdint.h>

namespace {

constexpr int D = 576, HKV = 16, SK = 65536, DH = 128, FF = 4608, NMOD = 6 * D, NQ = 4096;
constexpr int R = 32;
constexpr int TPH = SK / R;
constexpr int TPH_SHIFT = 11;
constexpr int NT = HKV * TPH;
constexpr int S = 5;
constexpr int STAGE_BYTES = 2 * R * DH * 2;
constexpr int MAXG = 144;
constexpr int NJOB = 128;
constexpr int NMODA = 72;
constexpr int NREP = 8;
constexpr int NQ0 = 16;
constexpr int NMODB = 72;
constexpr int NRED = D / 8;
constexpr int ROWP = 1168;

constexpr int OFF_RING = 0;
constexpr int OFF_W1 = OFF_RING + S * STAGE_BYTES;
constexpr int W1_BYTES = 2 * 576 * 80;
constexpr int OFF_W2 = OFF_W1 + W1_BYTES;
constexpr int W2_BYTES = 32 * ROWP;
constexpr int OFF_UP = OFF_W1 + W1_BYTES / 2;
constexpr int OFF_QS = OFF_W2 + W2_BYTES;
constexpr int OFF_MB = OFF_QS + NQ * 2;
constexpr int MB_FLOATS = 4 * 2 * 132;
constexpr int OFF_SC = OFF_MB + 2 * MB_FLOATS * 4;
constexpr int OFF_VEC = OFF_SC + D * 2;
constexpr int OFF_RED = OFF_VEC + D * 2;
constexpr int OFF_SM = OFF_RED + 384 * 4;
constexpr int OFF_BAR = OFF_SM + 128;
constexpr int SMEM_BYTES = OFF_BAR + 384;
static_assert(SMEM_BYTES <= 232448, "smem");
static_assert(40 * ROWP <= S * STAGE_BYTES, "down fits ring");
static_assert(OFF_QS % 512 == 0 && OFF_W1 % 512 == 0, "swizzle alignment");

constexpr float SCALE = 0.08838834764831845f;
constexpr float LOG2E = 1.4426950408889634f;
#define TBATCH 1u
#define TEND 8u
#define PSLEEP 0
#define PFENCE 0
#define HW 2
constexpr unsigned SPIN_LIMIT = 1u << 22;

__device__ unsigned g_epoch;
__device__ unsigned g_ticket;
__device__ __align__(128) unsigned g_modA[NREP * 2 * D];
__device__ __align__(128) float g_modB[4 * D];
__device__ __align__(128) unsigned long long g_q[NQ / 2];
__device__ __align__(128) unsigned long long g_q0[NREP * NQ0 * 16];
__device__ __align__(128) float g_recO[HKV * 8 * MAXG * 32];
__device__ __align__(128) float g_recML[HKV * 2 * MAXG * 8];
__device__ __align__(128) float g_yp[NJOB * D];
__device__ __align__(128) unsigned g_x1[NREP * D];
__device__ __align__(128) float g_z[NJOB * D];

__device__ __forceinline__ uint32_t smem_u32(const void* p) { return (uint32_t)__cvta_generic_to_shared(p); }
__device__ __forceinline__ void mbar_init(uint32_t bar, uint32_t cnt) {
  asm volatile("mbarrier.init.shared::cta.b64 [%0], %1;" ::"r"(bar), "r"(cnt) : "memory");
}
__device__ __forceinline__ void mbar_expect_tx(uint32_t bar, uint32_t bytes) {
  asm volatile("mbarrier.arrive.expect_tx.shared::cta.b64 _, [%0], %1;" ::"r"(bar), "r"(bytes) : "memory");
}
__device__ __forceinline__ void mbar_arrive(uint32_t bar) {
  asm volatile("mbarrier.arrive.shared::cta.b64 _, [%0];" ::"r"(bar) : "memory");
}
__device__ __forceinline__ bool mbar_try(uint32_t bar, uint32_t parity) {
  uint32_t ok;
  asm volatile("{\n.reg .pred p;\nmbarrier.try_wait.parity.shared::cta.b64 p, [%1], %2;\nselp.u32 %0, 1, 0, p;\n}"
               : "=r"(ok) : "r"(bar), "r"(parity) : "memory");
  return ok != 0;
}
__device__ __forceinline__ void mbar_wait(uint32_t bar, uint32_t parity) {
  unsigned n = 0;
  while (!mbar_try(bar, parity)) {
    if (++n > SPIN_LIMIT) __trap();
  }
}
__device__ __forceinline__ uint64_t stream_policy() {
  uint64_t pol;
  asm volatile("createpolicy.fractional.L2::evict_first.b64 %0, 1.0;" : "=l"(pol));
  return pol;
}
__device__ __forceinline__ void bulk_load(uint32_t dst, const void* src, uint32_t bytes, uint32_t bar, uint64_t pol) {
  asm volatile("cp.async.bulk.shared::cluster.global.mbarrier::complete_tx::bytes.L2::cache_hint [%0], [%1], %2, [%3], %4;"
               ::"r"(dst), "l"(src), "r"(bytes), "r"(bar), "l"(pol) : "memory");
}
__device__ __forceinline__ void tma2d(uint32_t dst, const CUtensorMap* m, int c0, int c1, uint32_t bar, uint64_t pol) {
  asm volatile("cp.async.bulk.tensor.2d.shared::cluster.global.mbarrier::complete_tx::bytes.L2::cache_hint"
               " [%0], [%1, {%3,%4}], [%2], %5;"
               ::"r"(dst), "l"(m), "r"(bar), "r"(c0), "r"(c1), "l"(pol) : "memory");
}
__device__ __forceinline__ void tma3d(uint32_t dst, const CUtensorMap* m, int c0, int c1, int c2, uint32_t bar,
                                      uint64_t pol) {
  asm volatile("cp.async.bulk.tensor.3d.shared::cluster.global.mbarrier::complete_tx::bytes.L2::cache_hint"
               " [%0], [%1, {%3,%4,%5}], [%2], %6;"
               ::"r"(dst), "l"(m), "r"(bar), "r"(c0), "r"(c1), "r"(c2), "l"(pol) : "memory");
}
__device__ __forceinline__ void prefetch_map(const CUtensorMap* m) {
  asm volatile("prefetch.tensormap [%0];" ::"l"(m) : "memory");
}
__device__ __forceinline__ void named_sync(int id, int n) { asm volatile("bar.sync %0, %1;" ::"r"(id), "r"(n) : "memory"); }
__device__ __forceinline__ void ldsm4(uint32_t a, uint32_t& r0, uint32_t& r1, uint32_t& r2, uint32_t& r3) {
  asm volatile("ldmatrix.sync.aligned.m8n8.x4.shared.b16 {%0,%1,%2,%3}, [%4];"
               : "=r"(r0), "=r"(r1), "=r"(r2), "=r"(r3) : "r"(a) : "memory");
}
__device__ __forceinline__ void ldsm4t(uint32_t a, uint32_t& r0, uint32_t& r1, uint32_t& r2, uint32_t& r3) {
  asm volatile("ldmatrix.sync.aligned.m8n8.x4.trans.shared.b16 {%0,%1,%2,%3}, [%4];"
               : "=r"(r0), "=r"(r1), "=r"(r2), "=r"(r3) : "r"(a) : "memory");
}
__device__ __forceinline__ void ldsm2t(uint32_t a, uint32_t& r0, uint32_t& r1) {
  asm volatile("ldmatrix.sync.aligned.m8n8.x2.trans.shared.b16 {%0,%1}, [%2];"
               : "=r"(r0), "=r"(r1) : "r"(a) : "memory");
}
__device__ __forceinline__ void mma16816(float (&c)[4], uint32_t a0, uint32_t a1, uint32_t a2, uint32_t a3,
                                         uint32_t b0, uint32_t b1) {
  asm volatile("mma.sync.aligned.m16n8k16.row.col.f32.bf16.bf16.f32 {%0,%1,%2,%3}, {%4,%5,%6,%7}, {%8,%9}, {%0,%1,%2,%3};"
               : "+f"(c[0]), "+f"(c[1]), "+f"(c[2]), "+f"(c[3])
               : "r"(a0), "r"(a1), "r"(a2), "r"(a3), "r"(b0), "r"(b1));
}
__device__ __forceinline__ void mma1688(float (&c)[4], uint32_t a0, uint32_t a1, uint32_t b0) {
  asm volatile("mma.sync.aligned.m16n8k8.row.col.f32.bf16.bf16.f32 {%0,%1,%2,%3}, {%4,%5}, {%6}, {%0,%1,%2,%3};"
               : "+f"(c[0]), "+f"(c[1]), "+f"(c[2]), "+f"(c[3])
               : "r"(a0), "r"(a1), "r"(b0));
}
__device__ __forceinline__ uint32_t pack_bf2(float lo, float hi) {
  uint32_t r;
  asm("cvt.rn.bf16x2.f32 %0, %1, %2;" : "=r"(r) : "f"(hi), "f"(lo));
  return r;
}
__device__ __forceinline__ float bfr(float x) { return __uint_as_float(pack_bf2(0.f, x)); }
__device__ __forceinline__ float bf_lo(uint32_t w) { return __uint_as_float(w << 16); }
__device__ __forceinline__ float bf_hi(uint32_t w) { return __uint_as_float(w & 0xffff0000u); }
__device__ __forceinline__ float ex2(float x) {
  float r;
  asm("ex2.approx.ftz.f32 %0, %1;" : "=f"(r) : "f"(x));
  return r;
}
__device__ __forceinline__ float fsqrt(float x) {
  float r;
  asm("sqrt.approx.f32 %0, %1;" : "=f"(r) : "f"(x));
  return r;
}
__device__ __forceinline__ float silu(float x) { return __fdividef(x, 1.f + __expf(-x)); }
__device__ __forceinline__ void st_ll(unsigned long long* p, uint32_t v, uint32_t tag) {
  unsigned long long w = ((unsigned long long)tag << 32) | v;
  asm volatile("st.relaxed.gpu.global.b64 [%0], %1;" ::"l"(p), "l"(w) : "memory");
}
__device__ __forceinline__ uint2 ld_relaxed64v(const void* p) {
  uint2 w;
  asm volatile("ld.relaxed.gpu.global.v2.b32 {%0,%1}, [%2];" : "=r"(w.x), "=r"(w.y) : "l"(p) : "memory");
  return w;
}
__device__ __forceinline__ uint32_t ld_relaxed32(const void* p) {
  uint32_t w;
  asm volatile("ld.relaxed.gpu.global.b32 %0, [%1];" : "=r"(w) : "l"(p) : "memory");
  return w;
}
__device__ __forceinline__ uint4 ld_relaxed128(const void* p) {
  uint4 w;
  asm volatile("ld.relaxed.gpu.global.v4.b32 {%0,%1,%2,%3}, [%4];"
               : "=r"(w.x), "=r"(w.y), "=r"(w.z), "=r"(w.w) : "l"(p) : "memory");
  return w;
}
__device__ __forceinline__ void st_relaxed32(void* p, uint32_t v) {
  asm volatile("st.relaxed.gpu.global.b32 [%0], %1;" ::"l"(p), "r"(v) : "memory");
}
__device__ __forceinline__ void st_relaxed128(void* p, const uint4& w) {
  asm volatile("st.relaxed.gpu.global.v4.b32 [%0], {%1,%2,%3,%4};" ::"l"(p), "r"(w.x), "r"(w.y), "r"(w.z), "r"(w.w) : "memory");
}
__device__ __forceinline__ uint32_t tag2(float v, uint32_t tag) { return (__float_as_uint(v) & ~3u) | (tag & 3u); }
__device__ __forceinline__ bool ok2(uint32_t w, uint32_t tag) { return ((w ^ tag) & 3u) == 0u; }
__device__ __forceinline__ bool ok2(const uint4& w, uint32_t tag) {
  return (((w.x ^ tag) | (w.y ^ tag) | (w.z ^ tag) | (w.w ^ tag)) & 3u) == 0u;
}
__device__ __forceinline__ bool ok16(const uint4& w, uint32_t tag) {
  return (((w.x ^ tag) | (w.y ^ tag) | (w.z ^ tag) | (w.w ^ tag)) & 0xffffu) == 0u;
}
__device__ __forceinline__ void push_stores() {
}
__device__ __forceinline__ void spin_check(unsigned& n) {
  if (++n > SPIN_LIMIT) __trap();
}
__device__ __forceinline__ void add4(float (&a)[4], const uint4& w) {
  a[0] += __uint_as_float(w.x); a[1] += __uint_as_float(w.y); a[2] += __uint_as_float(w.z); a[3] += __uint_as_float(w.w);
}
__device__ __forceinline__ unsigned draw_tickets(unsigned n) {
  unsigned r, lane;
  asm volatile("mov.u32 %0, %%laneid;" : "=r"(lane));
  asm volatile("atom.relaxed.gpu.global.add.u32 %0, [%1], %2;" : "=r"(r) : "l"(&g_ticket + lane), "r"(n) : "memory");
  return r;
}
#define DBG_T(i) do { } while (0)

__device__ __noinline__ float gemv32(uint32_t wbase, const uint32_t* v32, int nks, int wi, int nw, float* red,
                                     int barid) {
  const int lane = threadIdx.x & 31, g = lane >> 2, t = lane & 3;
  float c0[4] = {0.f, 0.f, 0.f, 0.f}, c1[4] = {0.f, 0.f, 0.f, 0.f};
  const int rl = (lane & 7) + ((lane >> 4) << 3), ch = (lane >> 3) & 1;
  const uint32_t sw = (rl >> 1) & 3;
  const uint32_t a0 = wbase + rl * 64 + ((ch ^ sw) << 4), a1 = wbase + rl * 64 + (((2 + ch) ^ sw) << 4);
#pragma unroll 3
  for (int ks = wi; ks < nks; ks += nw) {
    uint32_t r0, r1, r2, r3, r4, r5, r6, r7;
    ldsm4t(a0 + ks * 1024, r0, r1, r2, r3);
    ldsm4t(a1 + ks * 1024, r4, r5, r6, r7);
    const uint32_t b0 = v32[ks * 8 + t], b1 = v32[ks * 8 + 4 + t];
    mma16816(c0, r0, r1, r2, r3, b0, b1);
    mma16816(c1, r4, r5, r6, r7, b0, b1);
  }
  if (t < 2) {
    red[wi * 32 + t * 8 + g] = t ? c0[2] : c0[0];
    red[wi * 32 + 16 + t * 8 + g] = t ? c1[2] : c1[0];
  }
  named_sync(barid, nw * 32);
  float r = 0.f;
  if (wi == 0)
    for (int w = 0; w < nw; w++) r += red[w * 32 + lane];
  return r;
}

template <int NW, bool K40>
__device__ __forceinline__ void gemv576(uint32_t wbase, float lo, float hi, bool k40, int wi, float* out, uint32_t tag) {
  constexpr int NT = (36 + NW - 1) / NW;
  const int lane = threadIdx.x & 31, g = lane >> 2, t = lane & 3;
  const uint32_t pk = pack_bf2(lo, __shfl_down_sync(0xffffffffu, lo, 1));
  const uint32_t b0 = __shfl_sync(0xffffffffu, pk, 2 * t), b1 = __shfl_sync(0xffffffffu, pk, 8 + 2 * t);
  const uint32_t b2 = __shfl_sync(0xffffffffu, pk, 16 + 2 * t), b3 = __shfl_sync(0xffffffffu, pk, 24 + 2 * t);
  uint32_t b4 = 0u;
  if (K40) {
    const uint32_t pk2 = pack_bf2(hi, __shfl_down_sync(0xffffffffu, hi, 1));
    b4 = __shfl_sync(0xffffffffu, pk2, 2 * t);
    if (!k40) b4 = 0u;
  }
  const uint32_t ra = wbase + ((lane & 7) + ((lane >> 4) << 3)) * ROWP + ((lane >> 3) & 1) * 16 + wi * 32;
  const uint32_t rb = wbase + (32 + (lane & 7)) * ROWP + ((lane >> 3) & 1) * 16 + wi * 32;
  const int last = (36 % NW != 0 && wi >= 36 % NW) ? (NT - 2) * NW * 32 : (NT - 1) * NW * 32;
  float c[NT][4];
  constexpr int CH = 3;
#pragma unroll
  for (int j0 = 0; j0 < NT; j0 += CH) {
    uint32_t r[CH][10];
#pragma unroll
    for (int j = j0; j < j0 + CH && j < NT; j++) {
      const uint32_t of = (j == NT - 1) ? last : j * NW * 32;
      uint32_t(&q)[10] = r[j - j0];
      ldsm4t(ra + of, q[0], q[1], q[2], q[3]);
      ldsm4t(ra + 16 * ROWP + of, q[4], q[5], q[6], q[7]);
      q[8] = q[9] = 0u;
      if (K40 && k40) ldsm2t(rb + of, q[8], q[9]);
    }
#pragma unroll
    for (int j = j0; j < j0 + CH && j < NT; j++) {
      c[j][0] = c[j][1] = c[j][2] = c[j][3] = 0.f;
      mma16816(c[j], r[j - j0][0], r[j - j0][1], r[j - j0][2], r[j - j0][3], b0, b1);
    }
#pragma unroll
    for (int j = j0; j < j0 + CH && j < NT; j++)
      mma16816(c[j], r[j - j0][4], r[j - j0][5], r[j - j0][6], r[j - j0][7], b2, b3);
    if (K40) {
#pragma unroll
      for (int j = j0; j < j0 + CH && j < NT; j++) mma1688(c[j], r[j - j0][8], r[j - j0][9], b4);
    }
  }
  if (t < 2) {
    float* o = out + wi * 16 + t * 8 + g;
#pragma unroll
    for (int j = 0; j < NT; j++)
      if (j < NT - 1 || 36 % NW == 0 || wi < 36 % NW) st_relaxed32(o + j * NW * 16, tag2(t ? c[j][2] : c[j][0], tag));
    push_stores();
  }
}

struct LnStats { float mb, den; };
__device__ __forceinline__ LnStats ln_stats(const float (&xa)[4], const float (&xb)[4], float* red, int warp, int lane) {
  const bool two = warp == 0 && lane < 16;
  float s = (xa[0] + xa[1]) + (xa[2] + xa[3]) + (xb[0] + xb[1]) + (xb[2] + xb[3]);
#pragma unroll
  for (int of = 16; of > 0; of >>= 1) s += __shfl_xor_sync(0xffffffffu, s, of);
  const float mw = s * (warp == 0 ? 1.f / 192.f : 1.f / 128.f);
  float v = 0.f;
#pragma unroll
  for (int j = 0; j < 4; j++) {
    const float d = xa[j] - mw, e = two ? xb[j] - mw : 0.f;
    v += d * d + e * e;
  }
#pragma unroll
  for (int of = 16; of > 0; of >>= 1) v += __shfl_xor_sync(0xffffffffu, v, of);
  if (lane == 0) { red[warp] = s; red[4 + warp] = v; }
  named_sync(3, 128);
  const float s0 = red[0], s1 = red[1], s2 = red[2], s3 = red[3];
  const float mean = ((s0 + s1) + (s2 + s3)) * (1.f / D);
  const float d0 = s0 * (1.f / 192.f) - mean, d1 = s1 * (1.f / 128.f) - mean;
  const float d2 = s2 * (1.f / 128.f) - mean, d3 = s3 * (1.f / 128.f) - mean;
  const float var = ((red[4] + red[5]) + (red[6] + red[7]) + 192.f * d0 * d0 + 128.f * (d1 * d1 + d2 * d2 + d3 * d3)) *
                    (1.f / D);
  LnStats r;
  r.mb = bfr(mean);
  r.den = bfr(fsqrt(bfr(bfr(var) + 1e-5f)));
  return r;
}
__device__ __forceinline__ uint2 ln_apply(const float (&x)[4], const LnStats& st, const uint4& scw, const uint4& shw) {
  const float sc[4] = {bf_hi(scw.x), bf_hi(scw.y), bf_hi(scw.z), bf_hi(scw.w)};
  const float sh[4] = {bf_hi(shw.x), bf_hi(shw.y), bf_hi(shw.z), bf_hi(shw.w)};
  float h[4];
#pragma unroll
  for (int j = 0; j < 4; j++) {
    const float n = bfr(__fdividef(bfr(x[j] - st.mb), st.den));
    h[j] = bfr(n * bfr(1.f + sc[j])) + sh[j];
  }
  return make_uint2(pack_bf2(h[0], h[1]), pack_bf2(h[2], h[3]));
}

struct Params {
  const __nv_bfloat16* x;
  const __nv_bfloat16* c;
  const __nv_bfloat16* wo;
  const __nv_bfloat16* wdown;
  __nv_bfloat16* out;
};

enum { B_FULL = 0, B_EMPTY = S, B_MODA = 2 * S, B_WQ, B_MODB, B_WO, B_UP = B_WO + 2, B_GATE = B_UP + 3,
       B_DOWN = B_GATE + 3, B_Q0 = B_DOWN + 4, B_QALL, B_W1FREE2, B_MFULL0, B_MFULL1, B_MFREE0, B_MFREE1, B_UPFREE,
       B_W1FREE, B_COUNT };
static_assert(B_COUNT * 8 <= 336, "barrier area");

__global__ void __launch_bounds__(288, 1)
fused_kernel(const __grid_constant__ CUtensorMap mapK, const __grid_constant__ CUtensorMap mapV,
             const __grid_constant__ CUtensorMap mapModA, const __grid_constant__ CUtensorMap mapMod,
             const __grid_constant__ CUtensorMap mapWq,
             const __grid_constant__ CUtensorMap mapGate, const __grid_constant__ CUtensorMap mapUp,
             const Params p) {
  extern __shared__ __align__(1024) unsigned char sp[];
  const uint32_t sb = smem_u32(sp);
  if (sb & 1023u) __trap();
  const int tid = threadIdx.x, warp = tid >> 5, lane = tid & 31;
  const int cta = blockIdx.x, G = gridDim.x;
  const uint32_t bar0 = sb + OFF_BAR;
  auto BAR = [&](int i) { return bar0 + 8u * i; };
  volatile int* s_tile = reinterpret_cast<volatile int*>(sp + OFF_BAR + 336);
  volatile int* s_minfo = reinterpret_cast<volatile int*>(sp + OFF_BAR + 360);

  if (warp == 8) {
    const uint64_t pol = stream_policy();
    if (lane == 0) {
      DBG_T(0);
      prefetch_map(&mapModA);
      prefetch_map(&mapWq);
      prefetch_map(&mapK);
      prefetch_map(&mapV);
      for (int i = 0; i < S; i++) { mbar_init(BAR(B_FULL + i), 1); mbar_init(BAR(B_EMPTY + i), 4); }
      for (int i = B_MODA; i < B_Q0; i++) mbar_init(BAR(i), 1);
      for (int i = B_Q0; i < B_W1FREE; i++) mbar_init(BAR(i), 4);
      mbar_init(BAR(B_W1FREE), 8);
      asm volatile("fence.proxy.async.shared::cta;" ::: "memory");
      if (cta < NMODA) {
        mbar_expect_tx(BAR(B_MODA), 576 * 32);
        for (int i = 0; i < 3; i++) tma2d(sb + OFF_UP + i * 6144, &mapModA, cta * 16, i * 192, BAR(B_MODA), pol);
      }
    }
    __syncthreads();
    if (lane == 0) {
      auto load_tile = [&](int stage, int tile) {
        s_tile[stage] = tile;
        mbar_expect_tx(BAR(B_FULL + stage), STAGE_BYTES);
        tma3d(sb + OFF_RING + stage * STAGE_BYTES, &mapK, 0, tile * R, 0, BAR(B_FULL + stage), pol);
        tma3d(sb + OFF_RING + stage * STAGE_BYTES + 8192, &mapV, 0, tile * R, 0, BAR(B_FULL + stage), pol);
      };
      if (cta < NJOB) {
        mbar_expect_tx(BAR(B_WQ), 576 * 64);
        for (int i = 0; i < 3; i++) tma2d(sb + OFF_W1 + i * 12288, &mapWq, cta * 32, i * 192, BAR(B_WQ), pol);
      }
      const unsigned ntd = NT - S * G;
      unsigned ncnt = TBATCH, nbase = draw_tickets(TBATCH);
      const int ustart = 72 * (cta >> 1) + 40 * (cta & 1);
      const bool job = cta < NJOB;
      auto head_chunk = [&](int i) {
        if (i < S) {
          load_tile(i, i * G + cta);
        } else if (job) {
          if (i < S + 2) {
            const int j = i - S;
            mbar_expect_tx(BAR(B_WO + j), 16 * 1152);
            for (int r = 16 * j; r < 16 * j + 16; r++)
              bulk_load(sb + OFF_W2 + r * ROWP, p.wo + (size_t)(cta * 32 + r) * D, 1152, BAR(B_WO + j), pol);
          } else {
            const int j = i - S - 2;
            if (j == 0 && cta < NMODA) mbar_wait(BAR(B_UPFREE), 0);
            mbar_expect_tx(BAR(B_UP + j), 192 * 80);
            tma2d(sb + OFF_UP + j * 15360, &mapUp, ustart, j * 192, BAR(B_UP + j), pol);
          }
        }
      };
      auto head_bar = [&](int i) { return i < S ? B_FULL + i : B_WO + (i - S); };
      if (cta < NMODA) mbar_wait(BAR(B_MODA), 0);
      prefetch_map(&mapUp);
#pragma unroll 1
      for (int i = 0; i < S + 5; i++) {
        if (i == HW - 1 && job) { mbar_wait(BAR(B_WQ), 0); }
        if (i >= HW && (job || i - HW < S)) mbar_wait(BAR(head_bar(i - HW)), 0);
        head_chunk(i);
      }
      prefetch_map(&mapMod);
      prefetch_map(&mapGate);
      if (cta < NMODB) {
        mbar_wait(BAR(B_W1FREE), 0);
        mbar_expect_tx(BAR(B_MODB), 576 * 64);
        for (int i = 0; i < 3; i++) tma2d(sb + OFF_W1 + i * 12288, &mapMod, 2 * D + cta * 32, i * 192, BAR(B_MODB), pol);
      }
      int stage = 0;
      uint32_t ph = 0;
      while (true) {
        const unsigned base = nbase, cnt = ncnt;
        if (base >= ntd) break;
        ncnt = (base + TEND * G < ntd) ? TBATCH : 1u;
        nbase = draw_tickets(ncnt);
#pragma unroll 1
        for (unsigned d = base; d < base + cnt && d < ntd; d++) {
          mbar_wait(BAR(B_EMPTY + stage), ph);
          load_tile(stage, S * G + (int)d);
          if (++stage == S) { stage = 0; ph ^= 1; }
        }
      }
      DBG_T(1);
      mbar_wait(BAR(B_EMPTY + stage), ph);
      s_tile[stage] = -1;
      mbar_arrive(BAR(B_FULL + stage));
      if (job) {
        auto gate_chunk = [&](int j) {
          mbar_expect_tx(BAR(B_GATE + j), 192 * 80);
          tma2d(sb + OFF_W1 + j * 15360, &mapGate, ustart, j * 192, BAR(B_GATE + j), pol);
        };
        const int nr = (cta & 1) ? 8 : 10;
        auto down_chunk = [&](int j) {
          mbar_expect_tx(BAR(B_DOWN + j), nr * 1152);
          for (int r = nr * j; r < nr * j + nr; r++)
            bulk_load(sb + OFF_RING + r * ROWP, p.wdown + (size_t)(ustart + r) * D, 1152, BAR(B_DOWN + j), pol);
        };
        mbar_wait(BAR(B_W1FREE2), 0);
        gate_chunk(0);
        gate_chunk(1);
        mbar_wait(BAR(B_GATE), 0);
        gate_chunk(2);
        mbar_wait(BAR(B_EMPTY + stage), ph ^ 1u);
        down_chunk(0);
        down_chunk(1);
        mbar_wait(BAR(B_DOWN), 0);
        down_chunk(2);
        mbar_wait(BAR(B_DOWN + 1), 0);
        down_chunk(3);
      }
      DBG_T(2);
    }
    return;
  }

  uint32_t* vec32 = reinterpret_cast<uint32_t*>(sp + OFF_VEC);
  uint32_t* sc32 = reinterpret_cast<uint32_t*>(sp + OFF_SC);
  float* red = reinterpret_cast<float*>(sp + OFF_RED);
  float* mbuf = reinterpret_cast<float*>(sp + OFF_MB);
  const unsigned tag = *(volatile unsigned*)&g_epoch + 1u;
  const bool two = tid < 16;
  const int c0 = 4 * tid, c1 = 512 + 4 * tid;

  if (warp < 4) {
    float xa[4], xb[4] = {0.f, 0.f, 0.f, 0.f};
    {
      const uint2 a = *reinterpret_cast<const uint2*>(p.x + c0);
      xa[0] = bf_lo(a.x); xa[1] = bf_hi(a.x); xa[2] = bf_lo(a.y); xa[3] = bf_hi(a.y);
      if (two) {
        const uint2 b = *reinterpret_cast<const uint2*>(p.x + c1);
        xb[0] = bf_lo(b.x); xb[1] = bf_hi(b.x); xb[2] = bf_lo(b.y); xb[3] = bf_hi(b.y);
      }
    }
    __syncthreads();
    const LnStats st = ln_stats(xa, xb, red + 256, warp, lane);
    if (tid == 0) DBG_T(3);
    {
      const unsigned* ma = g_modA + (cta & (NREP - 1)) * 2 * D;
      uint4 w[4];
      unsigned n = 0;
      while (true) {
        w[0] = ld_relaxed128(ma + c0);
        w[1] = ld_relaxed128(ma + D + c0);
        bool ok = ok16(w[0], tag) && ok16(w[1], tag);
        if (two) {
          w[2] = ld_relaxed128(ma + c1);
          w[3] = ld_relaxed128(ma + D + c1);
          ok = ok && ok16(w[2], tag) && ok16(w[3], tag);
        }
        if (ok) break;
        spin_check(n);
      }
      *reinterpret_cast<uint2*>(vec32 + 2 * tid) = ln_apply(xa, st, w[1], w[0]);
      if (two) *reinterpret_cast<uint2*>(vec32 + 256 + 2 * tid) = ln_apply(xb, st, w[3], w[2]);
    }
  } else {
    const int st = tid - 128;
    if (st < 72) {
      const uint4 a = *reinterpret_cast<const uint4*>(p.c + st * 8);
      uint4 r;
      r.x = pack_bf2(silu(bf_lo(a.x)), silu(bf_hi(a.x))); r.y = pack_bf2(silu(bf_lo(a.y)), silu(bf_hi(a.y)));
      r.z = pack_bf2(silu(bf_lo(a.z)), silu(bf_hi(a.z))); r.w = pack_bf2(silu(bf_lo(a.w)), silu(bf_hi(a.w)));
      *reinterpret_cast<uint4*>(sc32 + st * 4) = r;
    }
    __syncthreads();
    if (cta < NMODA) {
      named_sync(2, 128);
      mbar_wait(BAR(B_MODA), 0);
      const int g = lane >> 2, t = lane & 3, sw = warp - 4;
      const uint32_t wa = sb + OFF_UP + ((lane & 7) + ((lane >> 4) << 3)) * 32 + ((lane >> 3) & 1) * 16;
      float c[3][4];
#pragma unroll
      for (int j = 0; j < 3; j++) { c[j][0] = c[j][1] = c[j][2] = c[j][3] = 0.f; }
#pragma unroll 1
      for (int k0 = sw; k0 < 36; k0 += 12) {
        uint32_t r[3][4], b[3][2];
#pragma unroll
        for (int j = 0; j < 3; j++) {
          ldsm4t(wa + (k0 + 4 * j) * 512, r[j][0], r[j][1], r[j][2], r[j][3]);
          b[j][0] = sc32[(k0 + 4 * j) * 8 + t]; b[j][1] = sc32[(k0 + 4 * j) * 8 + 4 + t];
        }
#pragma unroll
        for (int j = 0; j < 3; j++) mma16816(c[j], r[j][0], r[j][1], r[j][2], r[j][3], b[j][0], b[j][1]);
      }
      if (t < 2) red[sw * 16 + t * 8 + g] = t ? c[0][2] + c[1][2] + c[2][2] : c[0][0] + c[1][0] + c[2][0];
      __syncwarp();
      if (lane == 0) mbar_arrive(BAR(B_UPFREE));
      named_sync(2, 128);
      const int col = st & 15;
      const float r = (red[col] + red[16 + col]) + (red[32 + col] + red[48 + col]);
      st_relaxed32(&g_modA[(st >> 4) * 2 * D + cta * 16 + col], __float_as_uint(bfr(r)) | (tag & 0xffffu));
      push_stores();

    }
  }
  named_sync(1, 256);
  if (tid == 0) DBG_T(4);
  if (cta < NJOB) {
    mbar_wait(BAR(B_WQ), 0);
    const float r = gemv32(sb + OFF_W1, vec32, 36, warp, 8, red, 1);
    if (warp == 0) {
      const uint32_t pk = pack_bf2(r, __shfl_down_sync(0xffffffffu, r, 1));
      const uint32_t w = __shfl_sync(0xffffffffu, pk, 2 * (lane & 15));
      if (cta < NQ0) {
#pragma unroll
        for (int i = 0; i < NREP / 2; i++) st_ll(&g_q0[((lane >> 4) + 2 * i) * NQ0 * 16 + cta * 16 + (lane & 15)], w, tag);
      } else if (lane < 16) {
        st_ll(&g_q[cta * 16 + lane], w, tag);
      }
    }
    if (warp == 0) push_stores();

  }
  __syncwarp();
  if (lane == 0) mbar_arrive(BAR(B_W1FREE));

  if (warp < 4) {
    const int g = lane >> 2, t = lane & 3;
    const uint32_t* qs32 = reinterpret_cast<const uint32_t*>(sp + OFF_QS);
    uint32_t qf[16];
    float o[8][4];
    float m = -INFINITY, l = 0.f;
    int cur = -1, nflush = 0;
    const int key = warp * 8 + (lane & 7);
    uint32_t koff[4];
#pragma unroll
    for (int u = 0; u < 4; u++) {
      const int chunk = 4 * u + (lane >> 3);
      koff[u] = (chunk >> 3) * 4096 + key * 128 + (((chunk & 7) ^ (key & 7)) << 4);
    }
#pragma unroll
    for (int i = 0; i < 8; i++) { o[i][0] = o[i][1] = o[i][2] = o[i][3] = 0.f; }
#pragma unroll
    for (int i = 0; i < 16; i++) qf[i] = 0u;

    int stage = 0;
    uint32_t ph = 0;
    while (true) {
      mbar_wait(BAR(B_FULL + stage), ph);
      const int tile = s_tile[stage];
      const int head = (tile < 0) ? HKV : (tile >> TPH_SHIFT);
      if (head != cur) {
        if (cur >= 0 || head > 0) {
          const int pb = nflush & 1;
          if (nflush >= 2) mbar_wait(BAR(B_MFREE0 + pb), ((nflush >> 1) - 1) & 1);
          float* mb = mbuf + pb * MB_FLOATS + warp * 264;
          float lr = l;
          lr += __shfl_xor_sync(0xffffffffu, lr, 1);
          lr += __shfl_xor_sync(0xffffffffu, lr, 2);
          if (t == 0) {
#pragma unroll
            for (int i = 0; i < 8; i++) {
              mb[16 * i + g] = o[i][0];
              mb[132 + 16 * i + g] = o[i][1];
              mb[16 * i + 8 + g] = o[i][2];
              mb[132 + 16 * i + 8 + g] = o[i][3];
            }
            if (g < 2) { mb[g * 132 + 128] = m * LOG2E; mb[g * 132 + 129] = lr; }
          }
          if (warp == 0 && lane == 0) { s_minfo[pb * 2] = cur; s_minfo[pb * 2 + 1] = head; }
          __syncwarp();
          if (lane == 0) mbar_arrive(BAR(B_MFULL0 + pb));
          nflush++;
        }
        if (tile < 0) break;
        if (cur < 0 && tid == 0) DBG_T(13);
        cur = head;
        m = -INFINITY; l = 0.f;
#pragma unroll
        for (int i = 0; i < 8; i++) { o[i][0] = o[i][1] = o[i][2] = o[i][3] = 0.f; }
        mbar_wait(BAR(head < 2 ? B_Q0 : B_QALL), 0);
        if (g < 2) {
          const uint32_t* qh = qs32 + (2 * head + g) * 64;
#pragma unroll
          for (int s = 0; s < 8; s++) { qf[2 * s] = qh[8 * s + t]; qf[2 * s + 1] = qh[8 * s + 4 + t]; }
        }
        if (head == 0 && tid == 0) DBG_T(5);
      }
      const uint32_t kb = sb + OFF_RING + stage * STAGE_BYTES;
      uint32_t kr[16], vr[16];
#pragma unroll
      for (int u = 0; u < 4; u++) ldsm4(kb + koff[u], kr[4 * u], kr[4 * u + 1], kr[4 * u + 2], kr[4 * u + 3]);
#pragma unroll
      for (int u = 0; u < 4; u++) ldsm4t(kb + 8192 + koff[u], vr[4 * u], vr[4 * u + 1], vr[4 * u + 2], vr[4 * u + 3]);
      float sa[4] = {0.f, 0.f, 0.f, 0.f}, sbb[4] = {0.f, 0.f, 0.f, 0.f};
#pragma unroll
      for (int u = 0; u < 4; u++) {
        mma16816(sa, qf[4 * u], 0u, qf[4 * u + 1], 0u, kr[4 * u], kr[4 * u + 1]);
        mma16816(sbb, qf[4 * u + 2], 0u, qf[4 * u + 3], 0u, kr[4 * u + 2], kr[4 * u + 3]);
      }
      const uint32_t sraw = pack_bf2(sa[0] + sbb[0], sa[1] + sbb[1]);
      const uint32_t ssc = pack_bf2(bf_lo(sraw) * SCALE, bf_hi(sraw) * SCALE);
      const float s0 = bf_lo(ssc), s1 = bf_hi(ssc);
      float tm = fmaxf(s0, s1);
      tm = fmaxf(tm, __shfl_xor_sync(0xffffffffu, tm, 1));
      tm = fmaxf(tm, __shfl_xor_sync(0xffffffffu, tm, 2));
      const float mn = fmaxf(m, tm);
      if (__any_sync(0xffffffffu, g < 2 && mn > m)) {
        const float alpha = ex2((m - mn) * LOG2E);
        l *= alpha;
        const float a0 = __shfl_sync(0xffffffffu, alpha, 0), a1 = __shfl_sync(0xffffffffu, alpha, 4);
#pragma unroll
        for (int i = 0; i < 8; i++) { o[i][0] *= a0; o[i][1] *= a1; o[i][2] *= a0; o[i][3] *= a1; }
        m = mn;
      }
      float p0 = ex2((s0 - m) * LOG2E), p1 = ex2((s1 - m) * LOG2E);
      if (g >= 2) { p0 = 0.f; p1 = 0.f; }
      l += p0 + p1;
      const uint32_t pk = pack_bf2(p0, p1);
#pragma unroll
      for (int i = 0; i < 8; i++) mma1688(o[i], vr[2 * i], vr[2 * i + 1], pk);
      __syncwarp();
      if (lane == 0) mbar_arrive(BAR(B_EMPTY + stage));
      if (++stage == S) { stage = 0; ph ^= 1; }
    }
    __syncwarp();
    if (lane == 0) mbar_arrive(BAR(B_EMPTY + stage));
    if (tid == 0) DBG_T(6);
    if (cta >= NJOB) return;

    uint4 sb0, cb0, sb1, cb1;
    unsigned n = 0;
    sb0 = ld_relaxed128(&g_modB[D + c0]); cb0 = ld_relaxed128(&g_modB[2 * D + c0]);
    sb1 = sb0; cb1 = cb0;
    if (two) { sb1 = ld_relaxed128(&g_modB[D + c1]); cb1 = ld_relaxed128(&g_modB[2 * D + c1]); }
    if (cta < NRED) {
      const int col = cta * 8 + (tid & 1) * 4;
      const uint2 xw = *reinterpret_cast<const uint2*>(p.x + col);
      uint4 ga = ld_relaxed128(&g_modB[col]);
      const float* yp = g_yp + (size_t)(tid >> 1) * D + col;
      uint4 wa = ld_relaxed128(yp), wb = ld_relaxed128(yp + 64 * D);
      while (!ok2(wa, tag) || !ok2(wb, tag)) {
        spin_check(n);
        if (!ok2(wa, tag)) wa = ld_relaxed128(yp);
        if (!ok2(wb, tag)) wb = ld_relaxed128(yp + 64 * D);
      }
      if (tid == 0) DBG_T(14);
      float f[4] = {0.f, 0.f, 0.f, 0.f};
      add4(f, wa);
      add4(f, wb);
#pragma unroll
      for (int o = 2; o <= 16; o <<= 1)
#pragma unroll
        for (int i = 0; i < 4; i++) f[i] += __shfl_xor_sync(0xffffffffu, f[i], o);
      float* rp = red + 264;
      if (lane < 2) *reinterpret_cast<float4*>(rp + warp * 8 + lane * 4) = make_float4(f[0], f[1], f[2], f[3]);
      while (!ok2(ga, tag)) { spin_check(n); ga = ld_relaxed128(&g_modB[col]); }
      named_sync(3, 128);
      if (tid < 2 * NREP) {
        const float4* r4 = reinterpret_cast<const float4*>(rp) + (tid & 1);
        const float4 a = r4[0], b = r4[2], c = r4[4], d = r4[6];
        const uint32_t tg = tag & 0xffffu;
        uint4 w;
        w.x = __float_as_uint(bfr(bf_lo(xw.x) + bfr(bf_hi(ga.x) * bfr((a.x + b.x) + (c.x + d.x))))) | tg;
        w.y = __float_as_uint(bfr(bf_hi(xw.x) + bfr(bf_hi(ga.y) * bfr((a.y + b.y) + (c.y + d.y))))) | tg;
        w.z = __float_as_uint(bfr(bf_lo(xw.y) + bfr(bf_hi(ga.z) * bfr((a.z + b.z) + (c.z + d.z))))) | tg;
        w.w = __float_as_uint(bfr(bf_hi(xw.y) + bfr(bf_hi(ga.w) * bfr((a.w + b.w) + (c.w + d.w))))) | tg;
        st_relaxed128(&g_x1[(tid >> 1) * D + col], w);
        push_stores();
      }
      if (tid == 0) DBG_T(19);
    }
    float xa[4], xb[4] = {0.f, 0.f, 0.f, 0.f};
    {
      const unsigned* x1 = g_x1 + (cta & (NREP - 1)) * D;
      uint4 w0, w1;
      while (true) {
        w0 = ld_relaxed128(x1 + c0);
        bool ok = ok16(w0, tag);
        if (two) { w1 = ld_relaxed128(x1 + c1); ok = ok && ok16(w1, tag); }
        if (ok) break;
        spin_check(n);
      }
      xa[0] = bf_hi(w0.x); xa[1] = bf_hi(w0.y); xa[2] = bf_hi(w0.z); xa[3] = bf_hi(w0.w);
      if (two) { xb[0] = bf_hi(w1.x); xb[1] = bf_hi(w1.y); xb[2] = bf_hi(w1.z); xb[3] = bf_hi(w1.w); }
    }
    if (tid == 0) DBG_T(8);
    while (!(ok2(sb0, tag) && ok2(cb0, tag) && ok2(sb1, tag) && ok2(cb1, tag))) {
      spin_check(n);
      sb0 = ld_relaxed128(&g_modB[D + c0]); cb0 = ld_relaxed128(&g_modB[2 * D + c0]);
      if (two) { sb1 = ld_relaxed128(&g_modB[D + c1]); cb1 = ld_relaxed128(&g_modB[2 * D + c1]); }
    }
    const LnStats st = ln_stats(xa, xb, red + 256, warp, lane);
    if (tid == 0) DBG_T(25);
    uint32_t* x1s = reinterpret_cast<uint32_t*>(sp + OFF_QS);
    *reinterpret_cast<uint2*>(vec32 + 2 * tid) = ln_apply(xa, st, cb0, sb0);
    *reinterpret_cast<uint2*>(x1s + 2 * tid) = make_uint2(pack_bf2(xa[0], xa[1]), pack_bf2(xa[2], xa[3]));
    if (two) {
      *reinterpret_cast<uint2*>(vec32 + 256 + 2 * tid) = ln_apply(xb, st, cb1, sb1);
      *reinterpret_cast<uint2*>(x1s + 256 + 2 * tid) = make_uint2(pack_bf2(xb[0], xb[1]), pack_bf2(xb[2], xb[3]));
    }
  } else {
    const int st = tid - 128, sw = warp - 4;
    {
      uint32_t* qs32 = reinterpret_cast<uint32_t*>(sp + OFF_QS);
      unsigned n = 0;
      {
        const unsigned long long* q0 = g_q0 + (cta & (NREP - 1)) * NQ0 * 16 + st * 2;
        uint4 w = ld_relaxed128(q0);
        while (w.y != tag || w.w != tag) { spin_check(n); w = ld_relaxed128(q0); }
        *reinterpret_cast<uint2*>(qs32 + st * 2) = make_uint2(w.x, w.z);
        __syncwarp();
        if (lane == 0) mbar_arrive(BAR(B_Q0));
      }
      while (true) {
        uint4 w[7];
        bool ok = true;
#pragma unroll
        for (int k = 0; k < 7; k++) w[k] = ld_relaxed128(&g_q[(st + 128 * (k + 1)) * 2]);
#pragma unroll
        for (int k = 0; k < 7; k++) {
          ok = ok && w[k].y == tag && w[k].w == tag;
          *reinterpret_cast<uint2*>(qs32 + (st + 128 * (k + 1)) * 2) = make_uint2(w[k].x, w[k].z);
        }
        if (ok) break;
        spin_check(n);
        __nanosleep(200);
      }
      __syncwarp();
      if (lane == 0) mbar_arrive(BAR(B_QALL));
    }
    if (cta < NMODB) {
      mbar_wait(BAR(B_MODB), 0);
      const float r = gemv32(sb + OFF_W1, sc32, 36, sw, 4, red, 2);
      if (st < 32) st_relaxed32(&g_modB[cta * 32 + st], tag2(bfr(r), tag));
    }
    __syncwarp();
    if (lane == 0) mbar_arrive(BAR(B_W1FREE2));
    {
      const uint32_t bad = (tag + 2u) & 3u;
#pragma unroll 1
      for (int he = 0; he < 2 * HKV; he++) {
        st_relaxed32(&g_recO[((he * 4 + sw) * MAXG + cta) * 32 + lane], bad);
        if (st < 8) st_relaxed32(&g_recML[(he * MAXG + cta) * 8 + st], bad);
      }
      if (cta < NJOB) {
#pragma unroll 1
        for (int i = st; i < D; i += 128) { st_relaxed32(&g_yp[cta * D + i], bad); st_relaxed32(&g_z[cta * D + i], bad); }
      }
      if (cta < NRED && st < 8 * NREP) st_relaxed32(&g_x1[(st >> 3) * D + cta * 8 + (st & 7)], (tag - 1u) & 0xffffu);
    }
    const int jobhead = (cta < NJOB) ? (cta >> 3) : -1;
    int nflush = 0;
    while (true) {
      const int pb = nflush & 1;
      mbar_wait(BAR(B_MFULL0 + pb), (nflush >> 1) & 1);
      const int from = s_minfo[pb * 2], to = s_minfo[pb * 2 + 1];
      if (from >= 0) {
        const float* mb = mbuf + pb * MB_FLOATS;
#pragma unroll
        for (int e = 0; e < 2; e++) {
          float mw[4], M = -INFINITY;
#pragma unroll
          for (int w = 0; w < 4; w++) { mw[w] = mb[w * 264 + e * 132 + 128]; M = fmaxf(M, mw[w]); }
          float acc = 0.f, L = 0.f;
#pragma unroll
          for (int w = 0; w < 4; w++) {
            const float f = ex2(mw[w] - M);
            acc += f * mb[w * 264 + e * 132 + st];
            L += f * mb[w * 264 + e * 132 + 129];
          }
          st_relaxed32(&g_recO[(((from * 2 + e) * 4 + sw) * MAXG + cta) * 32 + lane], tag2(acc, tag));
          if (st < 8) st_relaxed32(&g_recML[((from * 2 + e) * MAXG + cta) * 8 + st], tag2(st == 0 ? M : L, tag));
        }
      }
      for (int h = from + 1; h < to; h++) {
#pragma unroll
        for (int e = 0; e < 2; e++) {
          st_relaxed32(&g_recO[(((h * 2 + e) * 4 + sw) * MAXG + cta) * 32 + lane], tag2(0.f, tag));
          if (st < 8) st_relaxed32(&g_recML[((h * 2 + e) * MAXG + cta) * 8 + st], tag2(st == 0 ? -1e30f : 0.f, tag));
        }
      }
      if (from >= HKV - 2) push_stores();
      __syncwarp();
      if (lane == 0) mbar_arrive(BAR(B_MFREE0 + pb));
      nflush++;
      if (jobhead >= 0 && jobhead >= from && jobhead < to) {
        const int he = cta >> 2, rr = cta & 3;
        const int i4 = st & 7, cg = st >> 3;
        const float* rO = g_recO + (size_t)(he * 4 + rr) * MAXG * 32 + i4 * 4;
        const float* rML = g_recML + (size_t)he * MAXG * 8;
        uint4 ov[9];
        uint2 ml[9];
        {
          unsigned n = 0;
          while (true) {
            bool ok = true;
#pragma unroll
            for (int k = 0; k < 9; k++) {
              const int c = cg + 16 * k;
              if (c < G) {
                ov[k] = ld_relaxed128(rO + c * 32);
                ml[k] = ld_relaxed64v(rML + c * 8);
              } else {
                ov[k] = make_uint4(tag & 3u, tag & 3u, tag & 3u, tag & 3u);
                ml[k] = make_uint2(tag2(-1e30f, tag), tag & 3u);
              }
            }
#pragma unroll
            for (int k = 0; k < 9; k++) ok = ok && ok2(ov[k], tag) && ok2(ml[k].x, tag) && ok2(ml[k].y, tag);
            if (ok) break;
            spin_check(n);
          }
        }
        if (st == 0) DBG_T(15);
        float M = __uint_as_float(ml[0].x);
#pragma unroll
        for (int k = 1; k < 9; k++) M = fmaxf(M, __uint_as_float(ml[k].x));
        M = fmaxf(M, __shfl_xor_sync(0xffffffffu, M, 8));
        M = fmaxf(M, __shfl_xor_sync(0xffffffffu, M, 16));
        float4 acc = make_float4(0.f, 0.f, 0.f, 0.f);
        float L = 0.f;
#pragma unroll
        for (int k = 0; k < 9; k++) {
          const float f = ex2(__uint_as_float(ml[k].x) - M);
          acc.x += f * __uint_as_float(ov[k].x); acc.y += f * __uint_as_float(ov[k].y);
          acc.z += f * __uint_as_float(ov[k].z); acc.w += f * __uint_as_float(ov[k].w);
          L += f * __uint_as_float(ml[k].y);
        }
#pragma unroll
        for (int o = 8; o <= 16; o <<= 1) {
          acc.x += __shfl_xor_sync(0xffffffffu, acc.x, o); acc.y += __shfl_xor_sync(0xffffffffu, acc.y, o);
          acc.z += __shfl_xor_sync(0xffffffffu, acc.z, o); acc.w += __shfl_xor_sync(0xffffffffu, acc.w, o);
          L += __shfl_xor_sync(0xffffffffu, L, o);
        }
        if (lane < 8) {
          float* rp = red + 64 + sw * 40;
          rp[lane * 4] = acc.x; rp[lane * 4 + 1] = acc.y; rp[lane * 4 + 2] = acc.z; rp[lane * 4 + 3] = acc.w;
          if (lane == 0) { rp[32] = L; rp[33] = M; }
        }
        if (cta == NJOB - 1 && st == 0) *(volatile unsigned*)&g_ticket = 0u;
        named_sync(2, 128);
        {
          const float* rp = red + 64;
          const float MM = fmaxf(fmaxf(rp[33], rp[73]), fmaxf(rp[113], rp[153]));
          const float f0 = ex2(rp[33] - MM), f1 = ex2(rp[73] - MM), f2 = ex2(rp[113] - MM), f3 = ex2(rp[153] - MM);
          const float num = f0 * rp[lane] + f1 * rp[40 + lane] + f2 * rp[80 + lane] + f3 * rp[120 + lane];
          const float den = f0 * rp[32] + f1 * rp[72] + f2 * rp[112] + f3 * rp[152];
          const float ov1 = __fdividef(num, den);
          mbar_wait(BAR(B_WO), 0);
          mbar_wait(BAR(B_WO + 1), 0);
          gemv576<4, false>(sb + OFF_W2, ov1, 0.f, false, sw, g_yp + (size_t)cta * D, tag);
        }

        if (st == 0) DBG_T(7);
      }
      if (to >= HKV) break;
    }
    if (cta >= NJOB) return;
  }
  uint32_t gbw = 0;
  if (cta < NRED && tid >= 128 && tid < 136) {
    unsigned n = 0;
    gbw = ld_relaxed32(&g_modB[3 * D + cta * 8 + tid - 128]);
    while (!ok2(gbw, tag)) { spin_check(n); gbw = ld_relaxed32(&g_modB[3 * D + cta * 8 + tid - 128]); }
  }
  named_sync(1, 256);
  if (tid == 0) DBG_T(9);

  {
    const int g = lane >> 2, t = lane & 3;
    const uint32_t rl = (lane & 7) + ((lane >> 4) << 3), ch = (lane >> 3) & 1;
    const uint32_t wb = sb + OFF_W1 + rl * 80;
    float acc[5][4];
#pragma unroll
    for (int n = 0; n < 5; n++) { acc[n][0] = acc[n][1] = acc[n][2] = acc[n][3] = 0.f; }
#pragma unroll 1
    for (int i = B_UP; i < B_DOWN; i++) mbar_wait(BAR(i), 0);
    if (tid == 0) DBG_T(20);
    uint32_t r[2][5][4], bv[2][2];
    auto load_k = [&](int buf, int ks) {
      bv[buf][0] = vec32[ks * 8 + t]; bv[buf][1] = vec32[ks * 8 + 4 + t];
#pragma unroll
      for (int n = 0; n < 5; n++) {
        const uint32_t ci = 2 * n + ch;
        const uint32_t off = (ci >= 5) ? W1_BYTES / 2 + (ci - 5) * 16 : ci * 16;
        ldsm4t(wb + ks * 1280 + off, r[buf][n][0], r[buf][n][1], r[buf][n][2], r[buf][n][3]);
      }
    };
    load_k(0, warp);
#pragma unroll
    for (int i = 0; i < 5; i++) {
      const bool more = i < 3 || (i == 3 && warp < 4);
      if (i < 4 && more) load_k((i + 1) & 1, warp + 8 * (i + 1));
      if (i < 4 || warp < 4) {
#pragma unroll
        for (int n = 0; n < 5; n++)
          mma16816(acc[n], r[i & 1][n][0], r[i & 1][n][1], r[i & 1][n][2], r[i & 1][n][3], bv[i & 1][0], bv[i & 1][1]);
      }
    }
    if (tid == 0) DBG_T(21);
    float* part = mbuf;
    if (t < 2) {
#pragma unroll
      for (int n = 0; n < 5; n++) part[warp * 80 + n * 16 + t * 8 + g] = t ? acc[n][2] : acc[n][0];
    }
    named_sync(1, 256);
    if (tid == 0) DBG_T(22);
    float g0 = 0.f, u0 = 0.f, g1 = 0.f, u1 = 0.f;
#pragma unroll
    for (int w = 0; w < 8; w++) {
      g0 += part[w * 80 + lane]; u0 += part[w * 80 + 40 + lane];
      g1 += part[w * 80 + 32 + (lane & 7)]; u1 += part[w * 80 + 72 + (lane & 7)];
    }
    const float alo = bfr(bfr(silu(bfr(g0))) * bfr(u0)), ahi = bfr(bfr(silu(bfr(g1))) * bfr(u1));
    if (tid == 0) DBG_T(10);
#pragma unroll 1
    for (int i = B_DOWN; i < B_DOWN + 4; i++) mbar_wait(BAR(i), 0);
    if (tid == 0) DBG_T(24);
    gemv576<8, true>(sb + OFF_RING, alo, ahi, (cta & 1) == 0, warp, g_z + (size_t)cta * D, tag);
  }
  if (tid == 0) DBG_T(11);
  if (cta < NRED) {
    const int j = tid >> 1, hf = tid & 1;
    const float* zp = g_z + (size_t)j * D + cta * 8 + hf * 4;
    uint4 w = ld_relaxed128(zp);
    unsigned n = 0;
    while (!ok2(w, tag)) { spin_check(n); w = ld_relaxed128(zp); }
    float f0 = __uint_as_float(w.x), f1 = __uint_as_float(w.y), f2 = __uint_as_float(w.z), f3 = __uint_as_float(w.w);
#pragma unroll
    for (int o = 2; o <= 16; o <<= 1) {
      f0 += __shfl_xor_sync(0xffffffffu, f0, o); f1 += __shfl_xor_sync(0xffffffffu, f1, o);
      f2 += __shfl_xor_sync(0xffffffffu, f2, o); f3 += __shfl_xor_sync(0xffffffffu, f3, o);
    }
    float* rp = red + 320;
    if (lane < 2) {
      rp[warp * 8 + lane * 4] = f0; rp[warp * 8 + lane * 4 + 1] = f1;
      rp[warp * 8 + lane * 4 + 2] = f2; rp[warp * 8 + lane * 4 + 3] = f3;
    }
    named_sync(1, 256);
    if (tid >= 128 && tid < 136) {
      const int i = tid - 128;
      float s = 0.f;
#pragma unroll
      for (int w8 = 0; w8 < 8; w8++) s += rp[w8 * 8 + i];
      const int col = cta * 8 + i;
      const float x1 = __bfloat162float(reinterpret_cast<const __nv_bfloat16*>(sp + OFF_QS)[col]);
      p.out[col] = __float2bfloat16_rn(x1 + bfr(bf_hi(gbw) * bfr(s)));
    }
    if (cta == 0 && tid == 0) *(volatile unsigned*)&g_epoch = tag;
  }
  if (tid == 0) DBG_T(12);
}

typedef CUresult (*EncodeFn)(CUtensorMap*, CUtensorMapDataType, cuuint32_t, void*, const cuuint64_t*, const cuuint64_t*,
                             const cuuint32_t*, const cuuint32_t*, CUtensorMapInterleave, CUtensorMapSwizzle,
                             CUtensorMapL2promotion, CUtensorMapFloatOOBfill);

CUtensorMap make_map(EncodeFn enc, const void* base, int rank, const cuuint64_t* dims, const cuuint64_t* strides,
                     const cuuint32_t* box, CUtensorMapSwizzle sw, CUtensorMapL2promotion pr) {
  CUtensorMap m;
  cuuint32_t es[3] = {1, 1, 1};
  enc(&m, CU_TENSOR_MAP_DATA_TYPE_BFLOAT16, rank, const_cast<void*>(base), dims, strides, box, es,
      CU_TENSOR_MAP_INTERLEAVE_NONE, sw, pr, CU_TENSOR_MAP_FLOAT_OOB_FILL_NONE);
  return m;
}

}

extern "C" void kernel_launch(void* const* d_in, const int* in_sizes, int n_in, void* d_out, int out_size) {
  (void)in_sizes; (void)n_in; (void)out_size;
  static EncodeFn enc = nullptr;
  static int nsm = 0;
  if (!enc) {
    void* fn = nullptr;
    cudaDriverEntryPointQueryResult qr;
    cudaGetDriverEntryPoint("cuTensorMapEncodeTiled", &fn, cudaEnableDefault, &qr);
    enc = (EncodeFn)fn;
    int dev = 0;
    cudaGetDevice(&dev);
    cudaDeviceGetAttribute(&nsm, cudaDevAttrMultiProcessorCount, dev);
    cudaFuncSetAttribute(fused_kernel, cudaFuncAttributeMaxDynamicSharedMemorySize, SMEM_BYTES);
  }
  CUtensorMap mK, mV, mModA, mMod, mWq, mG, mU;
  {
    cuuint64_t dims[3] = {64, (cuuint64_t)HKV * SK, 2};
    cuuint64_t str[2] = {256, 128};
    cuuint32_t box[3] = {64, R, 2};
    mK = make_map(enc, d_in[1], 3, dims, str, box, CU_TENSOR_MAP_SWIZZLE_128B, CU_TENSOR_MAP_L2_PROMOTION_L2_256B);
    mV = make_map(enc, d_in[2], 3, dims, str, box, CU_TENSOR_MAP_SWIZZLE_128B, CU_TENSOR_MAP_L2_PROMOTION_L2_256B);
  }
  {
    cuuint64_t dims[2] = {NMOD, D};
    cuuint64_t str[1] = {NMOD * 2};
    cuuint32_t box[2] = {32, 192};
    mMod = make_map(enc, d_in[10], 2, dims, str, box, CU_TENSOR_MAP_SWIZZLE_64B, CU_TENSOR_MAP_L2_PROMOTION_L2_256B);
    cuuint32_t boxa[2] = {16, 192};
    mModA = make_map(enc, d_in[10], 2, dims, str, boxa, CU_TENSOR_MAP_SWIZZLE_NONE, CU_TENSOR_MAP_L2_PROMOTION_L2_256B);
  }
  {
    cuuint64_t dims[2] = {NQ, D};
    cuuint64_t str[1] = {NQ * 2};
    cuuint32_t box[2] = {32, 192};
    mWq = make_map(enc, d_in[3], 2, dims, str, box, CU_TENSOR_MAP_SWIZZLE_64B, CU_TENSOR_MAP_L2_PROMOTION_L2_256B);
  }
  {
    cuuint64_t dims[2] = {FF, D};
    cuuint64_t str[1] = {FF * 2};
    cuuint32_t box[2] = {40, 192};
    mG = make_map(enc, d_in[6], 2, dims, str, box, CU_TENSOR_MAP_SWIZZLE_NONE, CU_TENSOR_MAP_L2_PROMOTION_L2_256B);
    mU = make_map(enc, d_in[7], 2, dims, str, box, CU_TENSOR_MAP_SWIZZLE_NONE, CU_TENSOR_MAP_L2_PROMOTION_L2_256B);
  }
  Params p;
  p.x = (const __nv_bfloat16*)d_in[0];
  p.c = (const __nv_bfloat16*)d_in[9];
  p.wo = (const __nv_bfloat16*)d_in[4];
  p.wdown = (const __nv_bfloat16*)d_in[8];
  p.out = (__nv_bfloat16*)d_out;
  int G = nsm < MAXG ? nsm : MAXG;
  fused_kernel<<<G, 288, SMEM_BYTES, cudaStreamPerThread>>>(mK, mV, mModA, mMod, mWq, mG, mU, p);
}
```

```cpp
#include <cuda_runtime.h>
#include <cuda_bf16.h>
#include <cuda.h>
#include <stdint.h>

namespace {

constexpr int D = 576, HKV = 16, SK = 65536, DH = 128, FF = 4608, NMOD = 6 * D, NQ = 4096;
constexpr int R = 32;
constexpr int TPH = SK / R;
constexpr int TPH_SHIFT = 11;
constexpr int NT = HKV * TPH;
constexpr int S = 5;
constexpr int STAGE_BYTES = 2 * R * DH * 2;
constexpr int MAXG = 144;
constexpr int NJOB = 128;
constexpr int NMODA = 72;
constexpr int NREP = 8;
constexpr int NQ0 = 16;
constexpr int NMODB = 72;
constexpr int NEARLY = HKV * 8 - 8;
constexpr int NRED = D / 8;
constexpr int ROWP = 1168;

constexpr int OFF_RING = 0;
constexpr int OFF_W1 = OFF_RING + S * STAGE_BYTES;
constexpr int W1_BYTES = 2 * 576 * 80;
constexpr int OFF_W2 = OFF_W1 + W1_BYTES;
constexpr int W2_BYTES = 32 * ROWP;
constexpr int OFF_UP = OFF_W1 + W1_BYTES / 2;
constexpr int OFF_QS = OFF_W2 + W2_BYTES;
constexpr int OFF_MB = OFF_QS + NQ * 2;
constexpr int MB_FLOATS = 4 * 2 * 132;
constexpr int OFF_SC = OFF_MB + 2 * MB_FLOATS * 4;
constexpr int OFF_VEC = OFF_SC + D * 2;
constexpr int OFF_RED = OFF_VEC + D * 2;
constexpr int OFF_SM = OFF_RED + 384 * 4;
constexpr int OFF_BAR = OFF_SM + 128;
constexpr int SMEM_BYTES = OFF_BAR + 384;
static_assert(SMEM_BYTES <= 232448, "smem");
static_assert(40 * ROWP <= S * STAGE_BYTES, "down fits ring");
static_assert(OFF_QS % 512 == 0 && OFF_W1 % 512 == 0, "swizzle alignment");

constexpr float SCALE = 0.08838834764831845f;
constexpr float LOG2E = 1.4426950408889634f;
constexpr unsigned TBATCH = 1u;
constexpr unsigned TEND = 8u;
constexpr unsigned RD = 1800u;
constexpr unsigned ZD = 1000u;
constexpr int HW = 2;
constexpr int CLAIM = 13;
constexpr unsigned SPIN_LIMIT = 1u << 22;

__device__ unsigned g_epoch;
__device__ unsigned g_ticket;
__device__ __align__(128) unsigned g_modA[NREP * 2 * D];
__device__ __align__(128) float g_modB[4 * D];
__device__ __align__(128) unsigned long long g_q[NQ / 2];
__device__ __align__(128) unsigned long long g_q0[NREP * NQ0 * 16];
__device__ __align__(128) float g_recO[HKV * 8 * MAXG * 32];
__device__ __align__(128) float g_recML[HKV * 2 * MAXG * 8];
__device__ __align__(128) float g_yp[NJOB * D];
__device__ __align__(128) float g_ye[NREP * D];
__device__ __align__(128) unsigned g_flag[NREP * 32];
__device__ __align__(128) float g_z[NJOB * D];

__device__ __forceinline__ uint32_t smem_u32(const void* p) { return (uint32_t)__cvta_generic_to_shared(p); }
__device__ __forceinline__ void mbar_init(uint32_t bar, uint32_t cnt) {
  asm volatile("mbarrier.init.shared::cta.b64 [%0], %1;" ::"r"(bar), "r"(cnt) : "memory");
}
__device__ __forceinline__ void mbar_expect_tx(uint32_t bar, uint32_t bytes) {
  asm volatile("mbarrier.arrive.expect_tx.shared::cta.b64 _, [%0], %1;" ::"r"(bar), "r"(bytes) : "memory");
}
__device__ __forceinline__ void mbar_arrive(uint32_t bar) {
  asm volatile("mbarrier.arrive.shared::cta.b64 _, [%0];" ::"r"(bar) : "memory");
}
__device__ __forceinline__ bool mbar_try(uint32_t bar, uint32_t parity) {
  uint32_t ok;
  asm volatile("{\n.reg .pred p;\nmbarrier.try_wait.parity.shared::cta.b64 p, [%1], %2;\nselp.u32 %0, 1, 0, p;\n}"
               : "=r"(ok) : "r"(bar), "r"(parity) : "memory");
  return ok != 0;
}
__device__ __forceinline__ void mbar_wait(uint32_t bar, uint32_t parity) {
  unsigned n = 0;
  while (!mbar_try(bar, parity)) {
    if (++n > SPIN_LIMIT) __trap();
  }
}
__device__ __forceinline__ uint64_t stream_policy() {
  uint64_t pol;
  asm volatile("createpolicy.fractional.L2::evict_first.b64 %0, 1.0;" : "=l"(pol));
  return pol;
}
__device__ __forceinline__ void bulk_load(uint32_t dst, const void* src, uint32_t bytes, uint32_t bar, uint64_t pol) {
  asm volatile("cp.async.bulk.shared::cluster.global.mbarrier::complete_tx::bytes.L2::cache_hint [%0], [%1], %2, [%3], %4;"
               ::"r"(dst), "l"(src), "r"(bytes), "r"(bar), "l"(pol) : "memory");
}
__device__ __forceinline__ void tma2d(uint32_t dst, const CUtensorMap* m, int c0, int c1, uint32_t bar, uint64_t pol) {
  asm volatile("cp.async.bulk.tensor.2d.shared::cluster.global.mbarrier::complete_tx::bytes.L2::cache_hint"
               " [%0], [%1, {%3,%4}], [%2], %5;"
               ::"r"(dst), "l"(m), "r"(bar), "r"(c0), "r"(c1), "l"(pol) : "memory");
}
__device__ __forceinline__ void tma3d(uint32_t dst, const CUtensorMap* m, int c0, int c1, int c2, uint32_t bar,
                                      uint64_t pol) {
  asm volatile("cp.async.bulk.tensor.3d.shared::cluster.global.mbarrier::complete_tx::bytes.L2::cache_hint"
               " [%0], [%1, {%3,%4,%5}], [%2], %6;"
               ::"r"(dst), "l"(m), "r"(bar), "r"(c0), "r"(c1), "r"(c2), "l"(pol) : "memory");
}
__device__ __forceinline__ void prefetch_map(const CUtensorMap* m) {
  asm volatile("prefetch.tensormap [%0];" ::"l"(m) : "memory");
}
__device__ __forceinline__ void named_sync(int id, int n) { asm volatile("bar.sync %0, %1;" ::"r"(id), "r"(n) : "memory"); }
__device__ __forceinline__ void ldsm4(uint32_t a, uint32_t& r0, uint32_t& r1, uint32_t& r2, uint32_t& r3) {
  asm volatile("ldmatrix.sync.aligned.m8n8.x4.shared.b16 {%0,%1,%2,%3}, [%4];"
               : "=r"(r0), "=r"(r1), "=r"(r2), "=r"(r3) : "r"(a) : "memory");
}
__device__ __forceinline__ void ldsm4t(uint32_t a, uint32_t& r0, uint32_t& r1, uint32_t& r2, uint32_t& r3) {
  asm volatile("ldmatrix.sync.aligned.m8n8.x4.trans.shared.b16 {%0,%1,%2,%3}, [%4];"
               : "=r"(r0), "=r"(r1), "=r"(r2), "=r"(r3) : "r"(a) : "memory");
}
__device__ __forceinline__ void ldsm2t(uint32_t a, uint32_t& r0, uint32_t& r1) {
  asm volatile("ldmatrix.sync.aligned.m8n8.x2.trans.shared.b16 {%0,%1}, [%2];"
               : "=r"(r0), "=r"(r1) : "r"(a) : "memory");
}
__device__ __forceinline__ void mma16816(float (&c)[4], uint32_t a0, uint32_t a1, uint32_t a2, uint32_t a3,
                                         uint32_t b0, uint32_t b1) {
  asm volatile("mma.sync.aligned.m16n8k16.row.col.f32.bf16.bf16.f32 {%0,%1,%2,%3}, {%4,%5,%6,%7}, {%8,%9}, {%0,%1,%2,%3};"
               : "+f"(c[0]), "+f"(c[1]), "+f"(c[2]), "+f"(c[3])
               : "r"(a0), "r"(a1), "r"(a2), "r"(a3), "r"(b0), "r"(b1));
}
__device__ __forceinline__ void mma1688(float (&c)[4], uint32_t a0, uint32_t a1, uint32_t b0) {
  asm volatile("mma.sync.aligned.m16n8k8.row.col.f32.bf16.bf16.f32 {%0,%1,%2,%3}, {%4,%5}, {%6}, {%0,%1,%2,%3};"
               : "+f"(c[0]), "+f"(c[1]), "+f"(c[2]), "+f"(c[3])
               : "r"(a0), "r"(a1), "r"(b0));
}
__device__ __forceinline__ uint32_t pack_bf2(float lo, float hi) {
  uint32_t r;
  asm("cvt.rn.bf16x2.f32 %0, %1, %2;" : "=r"(r) : "f"(hi), "f"(lo));
  return r;
}
__device__ __forceinline__ float bfr(float x) { return __uint_as_float(pack_bf2(0.f, x)); }
__device__ __forceinline__ float bf_lo(uint32_t w) { return __uint_as_float(w << 16); }
__device__ __forceinline__ float bf_hi(uint32_t w) { return __uint_as_float(w & 0xffff0000u); }
__device__ __forceinline__ float ex2(float x) {
  float r;
  asm("ex2.approx.ftz.f32 %0, %1;" : "=f"(r) : "f"(x));
  return r;
}
__device__ __forceinline__ float fsqrt(float x) {
  float r;
  asm("sqrt.approx.f32 %0, %1;" : "=f"(r) : "f"(x));
  return r;
}
__device__ __forceinline__ float silu(float x) { return __fdividef(x, 1.f + __expf(-x)); }
__device__ __forceinline__ void st_ll(unsigned long long* p, uint32_t v, uint32_t tag) {
  unsigned long long w = ((unsigned long long)tag << 32) | v;
  asm volatile("st.relaxed.gpu.global.b64 [%0], %1;" ::"l"(p), "l"(w) : "memory");
}
__device__ __forceinline__ uint2 ld_relaxed64v(const void* p) {
  uint2 w;
  asm volatile("ld.relaxed.gpu.global.v2.b32 {%0,%1}, [%2];" : "=r"(w.x), "=r"(w.y) : "l"(p) : "memory");
  return w;
}
__device__ __forceinline__ uint32_t ld_relaxed32(const void* p) {
  uint32_t w;
  asm volatile("ld.relaxed.gpu.global.b32 %0, [%1];" : "=r"(w) : "l"(p) : "memory");
  return w;
}
__device__ __forceinline__ uint4 ld_relaxed128(const void* p) {
  uint4 w;
  asm volatile("ld.relaxed.gpu.global.v4.b32 {%0,%1,%2,%3}, [%4];"
               : "=r"(w.x), "=r"(w.y), "=r"(w.z), "=r"(w.w) : "l"(p) : "memory");
  return w;
}
__device__ __forceinline__ void st_relaxed32(void* p, uint32_t v) {
  asm volatile("st.relaxed.gpu.global.b32 [%0], %1;" ::"l"(p), "r"(v) : "memory");
}
__device__ __forceinline__ void st_relaxed128(void* p, const uint4& w) {
  asm volatile("st.relaxed.gpu.global.v4.b32 [%0], {%1,%2,%3,%4};" ::"l"(p), "r"(w.x), "r"(w.y), "r"(w.z), "r"(w.w) : "memory");
}
__device__ __forceinline__ uint32_t tag2(float v, uint32_t tag) { return (__float_as_uint(v) & ~3u) | (tag & 3u); }
__device__ __forceinline__ bool ok2(uint32_t w, uint32_t tag) { return ((w ^ tag) & 3u) == 0u; }
__device__ __forceinline__ bool ok2(const uint4& w, uint32_t tag) {
  return (((w.x ^ tag) | (w.y ^ tag) | (w.z ^ tag) | (w.w ^ tag)) & 3u) == 0u;
}
__device__ __forceinline__ bool ok16(const uint4& w, uint32_t tag) {
  return (((w.x ^ tag) | (w.y ^ tag) | (w.z ^ tag) | (w.w ^ tag)) & 0xffffu) == 0u;
}
__device__ __forceinline__ void spin_check(unsigned& n) {
  if (++n > SPIN_LIMIT) __trap();
}
__device__ __forceinline__ void backoff(unsigned cycles) {
  const unsigned c = (unsigned)clock();
  while ((unsigned)clock() - c < cycles) { }
}
__device__ __forceinline__ void add4(float (&a)[4], const uint4& w) {
  a[0] += __uint_as_float(w.x); a[1] += __uint_as_float(w.y); a[2] += __uint_as_float(w.z); a[3] += __uint_as_float(w.w);
}
__device__ __forceinline__ unsigned draw_tickets(unsigned n) {
  unsigned r, lane;
  asm volatile("mov.u32 %0, %%laneid;" : "=r"(lane));
  asm volatile("atom.relaxed.gpu.global.add.u32 %0, [%1], %2;" : "=r"(r) : "l"(&g_ticket + lane), "r"(n) : "memory");
  return r;
}
#define DBG_T(i) do { } while (0)

__device__ __noinline__ float gemv32(uint32_t wbase, const uint32_t* v32, int nks, int wi, int nw, float* red,
                                     int barid) {
  const int lane = threadIdx.x & 31, g = lane >> 2, t = lane & 3;
  float c0[4] = {0.f, 0.f, 0.f, 0.f}, c1[4] = {0.f, 0.f, 0.f, 0.f};
  const int rl = (lane & 7) + ((lane >> 4) << 3), ch = (lane >> 3) & 1;
  const uint32_t sw = (rl >> 1) & 3;
  const uint32_t a0 = wbase + rl * 64 + ((ch ^ sw) << 4), a1 = wbase + rl * 64 + (((2 + ch) ^ sw) << 4);
#pragma unroll 3
  for (int ks = wi; ks < nks; ks += nw) {
    uint32_t r0, r1, r2, r3, r4, r5, r6, r7;
    ldsm4t(a0 + ks * 1024, r0, r1, r2, r3);
    ldsm4t(a1 + ks * 1024, r4, r5, r6, r7);
    const uint32_t b0 = v32[ks * 8 + t], b1 = v32[ks * 8 + 4 + t];
    mma16816(c0, r0, r1, r2, r3, b0, b1);
    mma16816(c1, r4, r5, r6, r7, b0, b1);
  }
  if (t < 2) {
    red[wi * 32 + t * 8 + g] = t ? c0[2] : c0[0];
    red[wi * 32 + 16 + t * 8 + g] = t ? c1[2] : c1[0];
  }
  named_sync(barid, nw * 32);
  float r = 0.f;
  if (wi == 0)
    for (int w = 0; w < nw; w++) r += red[w * 32 + lane];
  return r;
}

template <int NW, bool K40>
__device__ __forceinline__ void gemv576(uint32_t wbase, float lo, float hi, bool k40, int wi, float* out, uint32_t tag) {
  constexpr int NT = (36 + NW - 1) / NW;
  const int lane = threadIdx.x & 31, g = lane >> 2, t = lane & 3;
  const uint32_t pk = pack_bf2(lo, __shfl_down_sync(0xffffffffu, lo, 1));
  const uint32_t b0 = __shfl_sync(0xffffffffu, pk, 2 * t), b1 = __shfl_sync(0xffffffffu, pk, 8 + 2 * t);
  const uint32_t b2 = __shfl_sync(0xffffffffu, pk, 16 + 2 * t), b3 = __shfl_sync(0xffffffffu, pk, 24 + 2 * t);
  uint32_t b4 = 0u;
  if (K40) {
    const uint32_t pk2 = pack_bf2(hi, __shfl_down_sync(0xffffffffu, hi, 1));
    b4 = __shfl_sync(0xffffffffu, pk2, 2 * t);
    if (!k40) b4 = 0u;
  }
  const uint32_t ra = wbase + ((lane & 7) + ((lane >> 4) << 3)) * ROWP + ((lane >> 3) & 1) * 16 + wi * 32;
  const uint32_t rb = wbase + (32 + (lane & 7)) * ROWP + ((lane >> 3) & 1) * 16 + wi * 32;
  const int last = (36 % NW != 0 && wi >= 36 % NW) ? (NT - 2) * NW * 32 : (NT - 1) * NW * 32;
  float c[NT][4];
  constexpr int CH = 3;
#pragma unroll
  for (int j0 = 0; j0 < NT; j0 += CH) {
    uint32_t r[CH][10];
#pragma unroll
    for (int j = j0; j < j0 + CH && j < NT; j++) {
      const uint32_t of = (j == NT - 1) ? last : j * NW * 32;
      uint32_t(&q)[10] = r[j - j0];
      ldsm4t(ra + of, q[0], q[1], q[2], q[3]);
      ldsm4t(ra + 16 * ROWP + of, q[4], q[5], q[6], q[7]);
      q[8] = q[9] = 0u;
      if (K40 && k40) ldsm2t(rb + of, q[8], q[9]);
    }
#pragma unroll
    for (int j = j0; j < j0 + CH && j < NT; j++) {
      c[j][0] = c[j][1] = c[j][2] = c[j][3] = 0.f;
      mma16816(c[j], r[j - j0][0], r[j - j0][1], r[j - j0][2], r[j - j0][3], b0, b1);
    }
#pragma unroll
    for (int j = j0; j < j0 + CH && j < NT; j++)
      mma16816(c[j], r[j - j0][4], r[j - j0][5], r[j - j0][6], r[j - j0][7], b2, b3);
    if (K40) {
#pragma unroll
      for (int j = j0; j < j0 + CH && j < NT; j++) mma1688(c[j], r[j - j0][8], r[j - j0][9], b4);
    }
  }
  if (t < 2) {
    float* o = out + wi * 16 + t * 8 + g;
#pragma unroll
    for (int j = 0; j < NT; j++)
      if (j < NT - 1 || 36 % NW == 0 || wi < 36 % NW) st_relaxed32(o + j * NW * 16, tag2(t ? c[j][2] : c[j][0], tag));
  }
}

struct LnStats { float mb, den; };
__device__ __forceinline__ LnStats ln_stats(const float (&xa)[4], const float (&xb)[4], float* red, int warp, int lane) {
  const bool two = warp == 0 && lane < 16;
  float s = (xa[0] + xa[1]) + (xa[2] + xa[3]) + (xb[0] + xb[1]) + (xb[2] + xb[3]);
#pragma unroll
  for (int of = 16; of > 0; of >>= 1) s += __shfl_xor_sync(0xffffffffu, s, of);
  const float mw = s * (warp == 0 ? 1.f / 192.f : 1.f / 128.f);
  float v = 0.f;
#pragma unroll
  for (int j = 0; j < 4; j++) {
    const float d = xa[j] - mw, e = two ? xb[j] - mw : 0.f;
    v += d * d + e * e;
  }
#pragma unroll
  for (int of = 16; of > 0; of >>= 1) v += __shfl_xor_sync(0xffffffffu, v, of);
  if (lane == 0) { red[warp] = s; red[4 + warp] = v; }
  named_sync(3, 128);
  const float s0 = red[0], s1 = red[1], s2 = red[2], s3 = red[3];
  const float mean = ((s0 + s1) + (s2 + s3)) * (1.f / D);
  const float d0 = s0 * (1.f / 192.f) - mean, d1 = s1 * (1.f / 128.f) - mean;
  const float d2 = s2 * (1.f / 128.f) - mean, d3 = s3 * (1.f / 128.f) - mean;
  const float var = ((red[4] + red[5]) + (red[6] + red[7]) + 192.f * d0 * d0 + 128.f * (d1 * d1 + d2 * d2 + d3 * d3)) *
                    (1.f / D);
  LnStats r;
  r.mb = bfr(mean);
  r.den = bfr(fsqrt(bfr(bfr(var) + 1e-5f)));
  return r;
}
__device__ __forceinline__ uint2 ln_apply(const float (&x)[4], const LnStats& st, const uint4& scw, const uint4& shw) {
  const float sc[4] = {bf_hi(scw.x), bf_hi(scw.y), bf_hi(scw.z), bf_hi(scw.w)};
  const float sh[4] = {bf_hi(shw.x), bf_hi(shw.y), bf_hi(shw.z), bf_hi(shw.w)};
  float h[4];
#pragma unroll
  for (int j = 0; j < 4; j++) {
    const float n = bfr(__fdividef(bfr(x[j] - st.mb), st.den));
    h[j] = bfr(n * bfr(1.f + sc[j])) + sh[j];
  }
  return make_uint2(pack_bf2(h[0], h[1]), pack_bf2(h[2], h[3]));
}

struct Params {
  const __nv_bfloat16* x;
  const __nv_bfloat16* c;
  const __nv_bfloat16* wo;
  const __nv_bfloat16* wdown;
  __nv_bfloat16* out;
};

enum { B_FULL = 0, B_EMPTY = S, B_MODA = 2 * S, B_WQ, B_MODB, B_WO, B_UP = B_WO + 2, B_GATE = B_UP + 3,
       B_DOWN = B_GATE + 3, B_Q0 = B_DOWN + 4, B_QALL, B_W1FREE2, B_MFULL0, B_MFULL1, B_MFREE0, B_MFREE1, B_UPFREE,
       B_W1FREE, B_COUNT };
static_assert(B_COUNT * 8 <= 336, "barrier area");

__global__ void __launch_bounds__(288, 1)
fused_kernel(const __grid_constant__ CUtensorMap mapK, const __grid_constant__ CUtensorMap mapV,
             const __grid_constant__ CUtensorMap mapModA, const __grid_constant__ CUtensorMap mapMod,
             const __grid_constant__ CUtensorMap mapWq,
             const __grid_constant__ CUtensorMap mapGate, const __grid_constant__ CUtensorMap mapUp,
             const Params p) {
  extern __shared__ __align__(1024) unsigned char sp[];
  const uint32_t sb = smem_u32(sp);
  if (sb & 1023u) __trap();
  const int tid = threadIdx.x, warp = tid >> 5, lane = tid & 31;
  const int cta = blockIdx.x, G = gridDim.x;
  const uint32_t bar0 = sb + OFF_BAR;
  auto BAR = [&](int i) { return bar0 + 8u * i; };
  volatile int* s_tile = reinterpret_cast<volatile int*>(sp + OFF_BAR + 336);
  volatile int* s_minfo = reinterpret_cast<volatile int*>(sp + OFF_BAR + 360);

  if (warp == 8) {
    const uint64_t pol = stream_policy();
    if (lane == 0) {
      DBG_T(0);
      prefetch_map(&mapModA);
      prefetch_map(&mapWq);
      prefetch_map(&mapK);
      prefetch_map(&mapV);
      for (int i = 0; i < S; i++) { mbar_init(BAR(B_FULL + i), 1); mbar_init(BAR(B_EMPTY + i), 4); }
      for (int i = B_MODA; i < B_Q0; i++) mbar_init(BAR(i), 1);
      for (int i = B_Q0; i < B_W1FREE; i++) mbar_init(BAR(i), 4);
      mbar_init(BAR(B_W1FREE), 8);
      asm volatile("fence.proxy.async.shared::cta;" ::: "memory");
      if (cta < NMODA) {
        mbar_expect_tx(BAR(B_MODA), 576 * 32);
        for (int i = 0; i < 3; i++) tma2d(sb + OFF_UP + i * 6144, &mapModA, cta * 16, i * 192, BAR(B_MODA), pol);
      }
    }
    __syncthreads();
    if (lane == 0) {
      auto load_tile = [&](int stage, int tile) {
        s_tile[stage] = tile;
        mbar_expect_tx(BAR(B_FULL + stage), STAGE_BYTES);
        tma3d(sb + OFF_RING + stage * STAGE_BYTES, &mapK, 0, tile * R, 0, BAR(B_FULL + stage), pol);
        tma3d(sb + OFF_RING + stage * STAGE_BYTES + 8192, &mapV, 0, tile * R, 0, BAR(B_FULL + stage), pol);
      };
      if (cta < NJOB) {
        mbar_expect_tx(BAR(B_WQ), 576 * 64);
        for (int i = 0; i < 3; i++) tma2d(sb + OFF_W1 + i * 12288, &mapWq, cta * 32, i * 192, BAR(B_WQ), pol);
      }
      const unsigned ntd = NT - S * G;
      unsigned ncnt = TBATCH, nbase = draw_tickets(TBATCH);
      const int ustart = 72 * (cta >> 1) + 40 * (cta & 1);
      const bool job = cta < NJOB;
      auto head_chunk = [&](int i) {
        if (i < S) {
          load_tile(i, i * G + cta);
        } else if (job) {
          if (i < S + 2) {
            const int j = i - S;
            mbar_expect_tx(BAR(B_WO + j), 16 * 1152);
            for (int r = 16 * j; r < 16 * j + 16; r++)
              bulk_load(sb + OFF_W2 + r * ROWP, p.wo + (size_t)(cta * 32 + r) * D, 1152, BAR(B_WO + j), pol);
          } else {
            const int j = i - S - 2;
            if (j == 0 && cta < NMODA) mbar_wait(BAR(B_UPFREE), 0);
            mbar_expect_tx(BAR(B_UP + j), 192 * 80);
            tma2d(sb + OFF_UP + j * 15360, &mapUp, ustart, j * 192, BAR(B_UP + j), pol);
          }
        }
      };
      auto head_bar = [&](int i) { return i < S ? B_FULL + i : B_WO + (i - S); };
      if (cta < NMODA) mbar_wait(BAR(B_MODA), 0);
      prefetch_map(&mapUp);
#pragma unroll 1
      for (int i = 0; i < S + 5; i++) {
        if (i == HW - 1 && job) { mbar_wait(BAR(B_WQ), 0); }
        if (i >= HW && (job || i - HW < S)) mbar_wait(BAR(head_bar(i - HW)), 0);
        head_chunk(i);
      }
      prefetch_map(&mapMod);
      prefetch_map(&mapGate);
      if (cta < NMODB) {
        mbar_wait(BAR(B_W1FREE), 0);
        mbar_expect_tx(BAR(B_MODB), 576 * 64);
        for (int i = 0; i < 3; i++) tma2d(sb + OFF_W1 + i * 12288, &mapMod, 2 * D + cta * 32, i * 192, BAR(B_MODB), pol);
      }
      auto gate_chunk = [&](int j) {
        mbar_expect_tx(BAR(B_GATE + j), 192 * 80);
        tma2d(sb + OFF_W1 + j * 15360, &mapGate, ustart, j * 192, BAR(B_GATE + j), pol);
      };
      int stage = 0;
      uint32_t ph = 0;
      while (true) {
        const unsigned base = nbase, cnt = ncnt;
        if (base >= ntd) break;
        ncnt = (base + TEND * G < ntd) ? TBATCH : 1u;
        nbase = draw_tickets(ncnt);
#pragma unroll 1
        for (unsigned d = base; d < base + cnt && d < ntd; d++) {
          mbar_wait(BAR(B_EMPTY + stage), ph);
          load_tile(stage, S * G + (int)d);
          if (++stage == S) { stage = 0; ph ^= 1; }
        }
      }
      DBG_T(1);
      mbar_wait(BAR(B_EMPTY + stage), ph);
      s_tile[stage] = -1;
      mbar_arrive(BAR(B_FULL + stage));
      if (job) {
        const int nr = (cta & 1) ? 8 : 10;
        auto down_chunk = [&](int j) {
          mbar_expect_tx(BAR(B_DOWN + j), nr * 1152);
          for (int r = nr * j; r < nr * j + nr; r++)
            bulk_load(sb + OFF_RING + r * ROWP, p.wdown + (size_t)(ustart + r) * D, 1152, BAR(B_DOWN + j), pol);
        };
        mbar_wait(BAR(B_W1FREE2), 0);
        gate_chunk(0);
        gate_chunk(1);
        mbar_wait(BAR(B_GATE), 0);
        gate_chunk(2);
        mbar_wait(BAR(B_EMPTY + stage), ph ^ 1u);
        down_chunk(0);
        down_chunk(1);
        mbar_wait(BAR(B_DOWN), 0);
        down_chunk(2);
        mbar_wait(BAR(B_DOWN + 1), 0);
        down_chunk(3);
      }
      DBG_T(2);
    }
    return;
  }

  uint32_t* vec32 = reinterpret_cast<uint32_t*>(sp + OFF_VEC);
  uint32_t* sc32 = reinterpret_cast<uint32_t*>(sp + OFF_SC);
  float* red = reinterpret_cast<float*>(sp + OFF_RED);
  float* mbuf = reinterpret_cast<float*>(sp + OFF_MB);
  const unsigned tag = *(volatile unsigned*)&g_epoch + 1u;
  const bool two = tid < 16;
  const int c0 = 4 * tid, c1 = 512 + 4 * tid;

  if (warp < 4) {
    float xa[4], xb[4] = {0.f, 0.f, 0.f, 0.f};
    {
      const uint2 a = *reinterpret_cast<const uint2*>(p.x + c0);
      xa[0] = bf_lo(a.x); xa[1] = bf_hi(a.x); xa[2] = bf_lo(a.y); xa[3] = bf_hi(a.y);
      if (two) {
        const uint2 b = *reinterpret_cast<const uint2*>(p.x + c1);
        xb[0] = bf_lo(b.x); xb[1] = bf_hi(b.x); xb[2] = bf_lo(b.y); xb[3] = bf_hi(b.y);
      }
    }
    __syncthreads();
    const LnStats st = ln_stats(xa, xb, red + 256, warp, lane);
    if (tid == 0) DBG_T(3);
    {
      const unsigned* ma = g_modA + (cta & (NREP - 1)) * 2 * D;
      uint4 w[4];
      unsigned n = 0;
      while (true) {
        w[0] = ld_relaxed128(ma + c0);
        w[1] = ld_relaxed128(ma + D + c0);
        bool ok = ok16(w[0], tag) && ok16(w[1], tag);
        if (two) {
          w[2] = ld_relaxed128(ma + c1);
          w[3] = ld_relaxed128(ma + D + c1);
          ok = ok && ok16(w[2], tag) && ok16(w[3], tag);
        }
        if (ok) break;
        spin_check(n);
      }
      *reinterpret_cast<uint2*>(vec32 + 2 * tid) = ln_apply(xa, st, w[1], w[0]);
      if (two) *reinterpret_cast<uint2*>(vec32 + 256 + 2 * tid) = ln_apply(xb, st, w[3], w[2]);
    }
  } else {
    const int st = tid - 128;
    if (st < 72) {
      const uint4 a = *reinterpret_cast<const uint4*>(p.c + st * 8);
      uint4 r;
      r.x = pack_bf2(silu(bf_lo(a.x)), silu(bf_hi(a.x))); r.y = pack_bf2(silu(bf_lo(a.y)), silu(bf_hi(a.y)));
      r.z = pack_bf2(silu(bf_lo(a.z)), silu(bf_hi(a.z))); r.w = pack_bf2(silu(bf_lo(a.w)), silu(bf_hi(a.w)));
      *reinterpret_cast<uint4*>(sc32 + st * 4) = r;
    }
    __syncthreads();
    if (cta < NMODA) {
      named_sync(2, 128);
      mbar_wait(BAR(B_MODA), 0);
      const int g = lane >> 2, t = lane & 3, sw = warp - 4;
      const uint32_t wa = sb + OFF_UP + ((lane & 7) + ((lane >> 4) << 3)) * 32 + ((lane >> 3) & 1) * 16;
      float c[3][4];
#pragma unroll
      for (int j = 0; j < 3; j++) { c[j][0] = c[j][1] = c[j][2] = c[j][3] = 0.f; }
#pragma unroll 1
      for (int k0 = sw; k0 < 36; k0 += 12) {
        uint32_t r[3][4], b[3][2];
#pragma unroll
        for (int j = 0; j < 3; j++) {
          ldsm4t(wa + (k0 + 4 * j) * 512, r[j][0], r[j][1], r[j][2], r[j][3]);
          b[j][0] = sc32[(k0 + 4 * j) * 8 + t]; b[j][1] = sc32[(k0 + 4 * j) * 8 + 4 + t];
        }
#pragma unroll
        for (int j = 0; j < 3; j++) mma16816(c[j], r[j][0], r[j][1], r[j][2], r[j][3], b[j][0], b[j][1]);
      }
      if (t < 2) red[sw * 16 + t * 8 + g] = t ? c[0][2] + c[1][2] + c[2][2] : c[0][0] + c[1][0] + c[2][0];
      __syncwarp();
      if (lane == 0) mbar_arrive(BAR(B_UPFREE));
      named_sync(2, 128);
      const int col = st & 15;
      const float r = (red[col] + red[16 + col]) + (red[32 + col] + red[48 + col]);
      st_relaxed32(&g_modA[(st >> 4) * 2 * D + cta * 16 + col], __float_as_uint(bfr(r)) | (tag & 0xffffu));

    }
  }
  named_sync(1, 256);
  if (tid == 0) DBG_T(4);
  if (cta < NJOB) {
    mbar_wait(BAR(B_WQ), 0);
    const float r = gemv32(sb + OFF_W1, vec32, 36, warp, 8, red, 1);
    if (warp == 0) {
      const uint32_t pk = pack_bf2(r, __shfl_down_sync(0xffffffffu, r, 1));
      const uint32_t w = __shfl_sync(0xffffffffu, pk, 2 * (lane & 15));
      if (cta < NQ0) {
#pragma unroll
        for (int i = 0; i < NREP / 2; i++) st_ll(&g_q0[((lane >> 4) + 2 * i) * NQ0 * 16 + cta * 16 + (lane & 15)], w, tag);
      } else if (lane < 16) {
        st_ll(&g_q[cta * 16 + lane], w, tag);
      }
    }

  }
  __syncwarp();
  if (lane == 0) mbar_arrive(BAR(B_W1FREE));

  if (warp < 4) {
    const int g = lane >> 2, t = lane & 3;
    const uint32_t* qs32 = reinterpret_cast<const uint32_t*>(sp + OFF_QS);
    uint32_t qf[16];
    float o[8][4];
    float m = -INFINITY, l = 0.f;
    int cur = -1, nflush = 0;
    const int key = warp * 8 + (lane & 7);
    uint32_t koff[4];
#pragma unroll
    for (int u = 0; u < 4; u++) {
      const int chunk = 4 * u + (lane >> 3);
      koff[u] = (chunk >> 3) * 4096 + key * 128 + (((chunk & 7) ^ (key & 7)) << 4);
    }
#pragma unroll
    for (int i = 0; i < 8; i++) { o[i][0] = o[i][1] = o[i][2] = o[i][3] = 0.f; }
#pragma unroll
    for (int i = 0; i < 16; i++) qf[i] = 0u;
    if (cta < NRED && tid < 2 * NREP) {
      const uint32_t bad = (tag + 2u) & 3u;
      st_relaxed128(&g_ye[(tid >> 1) * D + cta * 8 + (tid & 1) * 4], make_uint4(bad, bad, bad, bad));
    }

    int stage = 0;
    uint32_t ph = 0;
    while (true) {
      mbar_wait(BAR(B_FULL + stage), ph);
      const int tile = s_tile[stage];
      const int head = (tile < 0) ? HKV : (tile >> TPH_SHIFT);
      if (head != cur) {
        if (cur >= 0 || head > 0) {
          const int pb = nflush & 1;
          if (nflush >= 2) mbar_wait(BAR(B_MFREE0 + pb), ((nflush >> 1) - 1) & 1);
          float* mb = mbuf + pb * MB_FLOATS + warp * 264;
          float lr = l;
          lr += __shfl_xor_sync(0xffffffffu, lr, 1);
          lr += __shfl_xor_sync(0xffffffffu, lr, 2);
          if (t == 0) {
#pragma unroll
            for (int i = 0; i < 8; i++) {
              mb[16 * i + g] = o[i][0];
              mb[132 + 16 * i + g] = o[i][1];
              mb[16 * i + 8 + g] = o[i][2];
              mb[132 + 16 * i + 8 + g] = o[i][3];
            }
            if (g < 2) { mb[g * 132 + 128] = m * LOG2E; mb[g * 132 + 129] = lr; }
          }
          if (warp == 0 && lane == 0) { s_minfo[pb * 2] = cur; s_minfo[pb * 2 + 1] = head; }
          __syncwarp();
          if (lane == 0) mbar_arrive(BAR(B_MFULL0 + pb));
          nflush++;
        }
        if (tile < 0) break;
        if (cur < 0 && tid == 0) DBG_T(13);
        cur = head;
        m = -INFINITY; l = 0.f;
#pragma unroll
        for (int i = 0; i < 8; i++) { o[i][0] = o[i][1] = o[i][2] = o[i][3] = 0.f; }
        mbar_wait(BAR(head < 2 ? B_Q0 : B_QALL), 0);
        if (g < 2) {
          const uint32_t* qh = qs32 + (2 * head + g) * 64;
#pragma unroll
          for (int s = 0; s < 8; s++) { qf[2 * s] = qh[8 * s + t]; qf[2 * s + 1] = qh[8 * s + 4 + t]; }
        }
        if (head == 0 && tid == 0) DBG_T(5);
      }
      const uint32_t kb = sb + OFF_RING + stage * STAGE_BYTES;
      uint32_t kr[16], vr[16];
#pragma unroll
      for (int u = 0; u < 4; u++) ldsm4(kb + koff[u], kr[4 * u], kr[4 * u + 1], kr[4 * u + 2], kr[4 * u + 3]);
#pragma unroll
      for (int u = 0; u < 4; u++) ldsm4t(kb + 8192 + koff[u], vr[4 * u], vr[4 * u + 1], vr[4 * u + 2], vr[4 * u + 3]);
      float sa[4] = {0.f, 0.f, 0.f, 0.f}, sbb[4] = {0.f, 0.f, 0.f, 0.f};
#pragma unroll
      for (int u = 0; u < 4; u++) {
        mma16816(sa, qf[4 * u], 0u, qf[4 * u + 1], 0u, kr[4 * u], kr[4 * u + 1]);
        mma16816(sbb, qf[4 * u + 2], 0u, qf[4 * u + 3], 0u, kr[4 * u + 2], kr[4 * u + 3]);
      }
      const uint32_t sraw = pack_bf2(sa[0] + sbb[0], sa[1] + sbb[1]);
      const uint32_t ssc = pack_bf2(bf_lo(sraw) * SCALE, bf_hi(sraw) * SCALE);
      const float s0 = bf_lo(ssc), s1 = bf_hi(ssc);
      float tm = fmaxf(s0, s1);
      tm = fmaxf(tm, __shfl_xor_sync(0xffffffffu, tm, 1));
      tm = fmaxf(tm, __shfl_xor_sync(0xffffffffu, tm, 2));
      const float mn = fmaxf(m, tm);
      if (__any_sync(0xffffffffu, g < 2 && mn > m)) {
        const float alpha = ex2((m - mn) * LOG2E);
        l *= alpha;
        const float a0 = __shfl_sync(0xffffffffu, alpha, 0), a1 = __shfl_sync(0xffffffffu, alpha, 4);
#pragma unroll
        for (int i = 0; i < 8; i++) { o[i][0] *= a0; o[i][1] *= a1; o[i][2] *= a0; o[i][3] *= a1; }
        m = mn;
      }
      float p0 = ex2((s0 - m) * LOG2E), p1 = ex2((s1 - m) * LOG2E);
      if (g >= 2) { p0 = 0.f; p1 = 0.f; }
      l += p0 + p1;
      const uint32_t pk = pack_bf2(p0, p1);
#pragma unroll
      for (int i = 0; i < 8; i++) mma1688(o[i], vr[2 * i], vr[2 * i + 1], pk);
      __syncwarp();
      if (lane == 0) mbar_arrive(BAR(B_EMPTY + stage));
      if (++stage == S) { stage = 0; ph ^= 1; }
    }
    __syncwarp();
    if (lane == 0) mbar_arrive(BAR(B_EMPTY + stage));
    if (tid == 0) DBG_T(6);
    if (cta >= NJOB) return;

    uint4 sb0, cb0, sb1, cb1;
    unsigned n = 0;
    sb0 = ld_relaxed128(&g_modB[D + c0]); cb0 = ld_relaxed128(&g_modB[2 * D + c0]);
    sb1 = sb0; cb1 = cb0;
    if (two) { sb1 = ld_relaxed128(&g_modB[D + c1]); cb1 = ld_relaxed128(&g_modB[2 * D + c1]); }
    uint2 xw0 = *reinterpret_cast<const uint2*>(p.x + c0), xw1 = xw0;
    uint4 ga0 = ld_relaxed128(&g_modB[c0]), ga1 = ga0;
    if (two) { xw1 = *reinterpret_cast<const uint2*>(p.x + c1); ga1 = ld_relaxed128(&g_modB[c1]); }
    if (cta < NRED) {
      const int j = tid >> 1;
      const float* yp = g_yp + (size_t)j * D + cta * 8 + (tid & 1) * 4;
      uint4 wa, wb = make_uint4(tag & 3u, tag & 3u, tag & 3u, tag & 3u);
      while (true) {
        wa = ld_relaxed128(yp);
        if (j + 64 < NEARLY) wb = ld_relaxed128(yp + 64 * D);
        if (ok2(wa, tag) && ok2(wb, tag)) break;
        spin_check(n);
      }
      float f[4] = {0.f, 0.f, 0.f, 0.f};
      add4(f, wa);
      add4(f, wb);
#pragma unroll
      for (int o = 2; o <= 16; o <<= 1)
#pragma unroll
        for (int i = 0; i < 4; i++) f[i] += __shfl_xor_sync(0xffffffffu, f[i], o);
      float* rp = red + 264;
      if (lane < 2) *reinterpret_cast<float4*>(rp + warp * 8 + lane * 4) = make_float4(f[0], f[1], f[2], f[3]);
      named_sync(3, 128);
      if (tid < 2 * NREP) {
        const float4* r4 = reinterpret_cast<const float4*>(rp) + (tid & 1);
        const float4 a = r4[0], b = r4[2], c = r4[4], d = r4[6];
        uint4 w;
        w.x = tag2((a.x + b.x) + (c.x + d.x), tag); w.y = tag2((a.y + b.y) + (c.y + d.y), tag);
        w.z = tag2((a.z + b.z) + (c.z + d.z), tag); w.w = tag2((a.w + b.w) + (c.w + d.w), tag);
        st_relaxed128(&g_ye[(tid >> 1) * D + cta * 8 + (tid & 1) * 4], w);
      }
      if (tid == 0) DBG_T(19);
    }
    while (!(ok2(ga0, tag) && ok2(sb0, tag) && ok2(cb0, tag) && ok2(ga1, tag) && ok2(sb1, tag) && ok2(cb1, tag))) {
      spin_check(n);
      ga0 = ld_relaxed128(&g_modB[c0]);
      sb0 = ld_relaxed128(&g_modB[D + c0]); cb0 = ld_relaxed128(&g_modB[2 * D + c0]);
      if (two) {
        ga1 = ld_relaxed128(&g_modB[c1]);
        sb1 = ld_relaxed128(&g_modB[D + c1]); cb1 = ld_relaxed128(&g_modB[2 * D + c1]);
      }
    }
    {
      const unsigned* fl = g_flag + (cta & (NREP - 1)) * 32 + (lane & 7);
      while (!__all_sync(0xffffffffu, ld_relaxed32(fl) == tag)) spin_check(n);
    }
    if (tid == 0) DBG_T(14);
    float xa[4], xb[4] = {0.f, 0.f, 0.f, 0.f};
    {
      const float* ye = g_ye + (cta & (NREP - 1)) * D;
      uint4 w[9], w2[9];
      const uint32_t bad = (tag + 2u) & 3u;
#pragma unroll
      for (int j = 0; j < 9; j++) {
        w[j] = make_uint4(bad, bad, bad, bad);
        w2[j] = two ? w[j] : make_uint4(tag & 3u, tag & 3u, tag & 3u, tag & 3u);
      }
      while (true) {
#pragma unroll
        for (int j = 0; j < 9; j++) {
          const float* src = j < 8 ? g_yp + (NEARLY + j) * D : ye;
          if (!ok2(w[j], tag)) w[j] = ld_relaxed128(src + c0);
          if (!ok2(w2[j], tag)) w2[j] = ld_relaxed128(src + c1);
        }
        bool ok = true;
#pragma unroll
        for (int j = 0; j < 9; j++) ok = ok && ok2(w[j], tag) && ok2(w2[j], tag);
        if (ok) break;
        spin_check(n);
      }
      float y0[4] = {0.f, 0.f, 0.f, 0.f}, y1[4] = {0.f, 0.f, 0.f, 0.f};
#pragma unroll
      for (int j = 0; j < 9; j++) add4(y0, w[j]);
      xa[0] = bfr(bf_lo(xw0.x) + bfr(bf_hi(ga0.x) * bfr(y0[0])));
      xa[1] = bfr(bf_hi(xw0.x) + bfr(bf_hi(ga0.y) * bfr(y0[1])));
      xa[2] = bfr(bf_lo(xw0.y) + bfr(bf_hi(ga0.z) * bfr(y0[2])));
      xa[3] = bfr(bf_hi(xw0.y) + bfr(bf_hi(ga0.w) * bfr(y0[3])));
      if (two) {
#pragma unroll
        for (int j = 0; j < 9; j++) add4(y1, w2[j]);
        xb[0] = bfr(bf_lo(xw1.x) + bfr(bf_hi(ga1.x) * bfr(y1[0])));
        xb[1] = bfr(bf_hi(xw1.x) + bfr(bf_hi(ga1.y) * bfr(y1[1])));
        xb[2] = bfr(bf_lo(xw1.y) + bfr(bf_hi(ga1.z) * bfr(y1[2])));
        xb[3] = bfr(bf_hi(xw1.y) + bfr(bf_hi(ga1.w) * bfr(y1[3])));
      }
    }
    if (tid == 0) DBG_T(8);
    const LnStats st = ln_stats(xa, xb, red + 256, warp, lane);
    if (tid == 0) DBG_T(25);
    uint32_t* x1s = reinterpret_cast<uint32_t*>(sp + OFF_QS);
    *reinterpret_cast<uint2*>(vec32 + 2 * tid) = ln_apply(xa, st, cb0, sb0);
    *reinterpret_cast<uint2*>(x1s + 2 * tid) = make_uint2(pack_bf2(xa[0], xa[1]), pack_bf2(xa[2], xa[3]));
    if (two) {
      *reinterpret_cast<uint2*>(vec32 + 256 + 2 * tid) = ln_apply(xb, st, cb1, sb1);
      *reinterpret_cast<uint2*>(x1s + 256 + 2 * tid) = make_uint2(pack_bf2(xb[0], xb[1]), pack_bf2(xb[2], xb[3]));
    }
  } else {
    const int st = tid - 128, sw = warp - 4;
    {
      uint32_t* qs32 = reinterpret_cast<uint32_t*>(sp + OFF_QS);
      unsigned n = 0;
      {
        const unsigned long long* q0 = g_q0 + (cta & (NREP - 1)) * NQ0 * 16 + st * 2;
        uint4 w = ld_relaxed128(q0);
        while (w.y != tag || w.w != tag) { spin_check(n); w = ld_relaxed128(q0); }
        *reinterpret_cast<uint2*>(qs32 + st * 2) = make_uint2(w.x, w.z);
        __syncwarp();
        if (lane == 0) mbar_arrive(BAR(B_Q0));
      }
      while (true) {
        uint4 w[7];
        bool ok = true;
#pragma unroll
        for (int k = 0; k < 7; k++) w[k] = ld_relaxed128(&g_q[(st + 128 * (k + 1)) * 2]);
#pragma unroll
        for (int k = 0; k < 7; k++) {
          ok = ok && w[k].y == tag && w[k].w == tag;
          *reinterpret_cast<uint2*>(qs32 + (st + 128 * (k + 1)) * 2) = make_uint2(w[k].x, w[k].z);
        }
        if (ok) break;
        spin_check(n);
        __nanosleep(200);
      }
      __syncwarp();
      if (lane == 0) mbar_arrive(BAR(B_QALL));
    }
    if (cta < NMODB) {
      mbar_wait(BAR(B_MODB), 0);
      const float r = gemv32(sb + OFF_W1, sc32, 36, sw, 4, red, 2);
      if (st < 32) st_relaxed32(&g_modB[cta * 32 + st], tag2(bfr(r), tag));
    }
    __syncwarp();
    if (lane == 0) mbar_arrive(BAR(B_W1FREE2));
    const int jobhead = (cta < NJOB) ? (cta >> 3) : -1;
    auto claim = [&](int h0) {
      const uint32_t bad = (tag + 2u) & 3u;
#pragma unroll 1
      for (int he = 2 * h0; he < 2 * HKV; he++) {
        st_relaxed32(&g_recO[((he * 4 + sw) * MAXG + cta) * 32 + lane], bad);
        if (st < 8) st_relaxed32(&g_recML[(he * MAXG + cta) * 8 + st], bad);
      }
      if (cta < NJOB) {
#pragma unroll 1
        for (int i = st; i < D; i += 128) {
          st_relaxed32(&g_z[cta * D + i], bad);
          if (jobhead >= h0) st_relaxed32(&g_yp[cta * D + i], bad);
        }
      }
      if (cta >= NEARLY && cta < NJOB && st < NREP) st_relaxed32(&g_flag[st * 32 + cta - NEARLY], tag - 1u);
    };
    claim(0);
    int nflush = 0;
    while (true) {
      const int pb = nflush & 1;
      mbar_wait(BAR(B_MFULL0 + pb), (nflush >> 1) & 1);
      const int from = s_minfo[pb * 2], to = s_minfo[pb * 2 + 1];
      if (from >= 0) {
        const float* mb = mbuf + pb * MB_FLOATS;
#pragma unroll
        for (int e = 0; e < 2; e++) {
          float mw[4], M = -INFINITY;
#pragma unroll
          for (int w = 0; w < 4; w++) { mw[w] = mb[w * 264 + e * 132 + 128]; M = fmaxf(M, mw[w]); }
          float acc = 0.f, L = 0.f;
#pragma unroll
          for (int w = 0; w < 4; w++) {
            const float f = ex2(mw[w] - M);
            acc += f * mb[w * 264 + e * 132 + st];
            L += f * mb[w * 264 + e * 132 + 129];
          }
          st_relaxed32(&g_recO[(((from * 2 + e) * 4 + sw) * MAXG + cta) * 32 + lane], tag2(acc, tag));
          if (st < 8) st_relaxed32(&g_recML[((from * 2 + e) * MAXG + cta) * 8 + st], tag2(st == 0 ? M : L, tag));
        }
      }
      for (int h = from + 1; h < to; h++) {
#pragma unroll
        for (int e = 0; e < 2; e++) {
          st_relaxed32(&g_recO[(((h * 2 + e) * 4 + sw) * MAXG + cta) * 32 + lane], tag2(0.f, tag));
          if (st < 8) st_relaxed32(&g_recML[((h * 2 + e) * MAXG + cta) * 8 + st], tag2(st == 0 ? -1e30f : 0.f, tag));
        }
      }
      if (from < CLAIM && to >= CLAIM && to < HKV) claim(to);
      __syncwarp();
      if (lane == 0) mbar_arrive(BAR(B_MFREE0 + pb));
      nflush++;
      if (jobhead >= 0 && jobhead >= from && jobhead < to) {
        const int he = cta >> 2, rr = cta & 3;
        const int i4 = st & 7, cg = st >> 3;
        const float* rO = g_recO + (size_t)(he * 4 + rr) * MAXG * 32 + i4 * 4;
        const float* rML = g_recML + (size_t)he * MAXG * 8;
        uint4 ov[9];
        uint2 ml[9];
        {
          backoff(RD);
          unsigned n = 0;
          while (true) {
            bool ok = true;
#pragma unroll
            for (int k = 0; k < 9; k++) {
              const int c = cg + 16 * k;
              if (c < G) {
                ov[k] = ld_relaxed128(rO + c * 32);
                ml[k] = ld_relaxed64v(rML + c * 8);
              } else {
                ov[k] = make_uint4(tag & 3u, tag & 3u, tag & 3u, tag & 3u);
                ml[k] = make_uint2(tag2(-1e30f, tag), tag & 3u);
              }
            }
#pragma unroll
            for (int k = 0; k < 9; k++) ok = ok && ok2(ov[k], tag) && ok2(ml[k].x, tag) && ok2(ml[k].y, tag);
            if (ok) break;
            spin_check(n);
          }
        }
        if (st == 0) DBG_T(15);
        float M = __uint_as_float(ml[0].x);
#pragma unroll
        for (int k = 1; k < 9; k++) M = fmaxf(M, __uint_as_float(ml[k].x));
        M = fmaxf(M, __shfl_xor_sync(0xffffffffu, M, 8));
        M = fmaxf(M, __shfl_xor_sync(0xffffffffu, M, 16));
        float4 acc = make_float4(0.f, 0.f, 0.f, 0.f);
        float L = 0.f;
#pragma unroll
        for (int k = 0; k < 9; k++) {
          const float f = ex2(__uint_as_float(ml[k].x) - M);
          acc.x += f * __uint_as_float(ov[k].x); acc.y += f * __uint_as_float(ov[k].y);
          acc.z += f * __uint_as_float(ov[k].z); acc.w += f * __uint_as_float(ov[k].w);
          L += f * __uint_as_float(ml[k].y);
        }
#pragma unroll
        for (int o = 8; o <= 16; o <<= 1) {
          acc.x += __shfl_xor_sync(0xffffffffu, acc.x, o); acc.y += __shfl_xor_sync(0xffffffffu, acc.y, o);
          acc.z += __shfl_xor_sync(0xffffffffu, acc.z, o); acc.w += __shfl_xor_sync(0xffffffffu, acc.w, o);
          L += __shfl_xor_sync(0xffffffffu, L, o);
        }
        if (lane < 8) {
          float* rp = red + 64 + sw * 40;
          rp[lane * 4] = acc.x; rp[lane * 4 + 1] = acc.y; rp[lane * 4 + 2] = acc.z; rp[lane * 4 + 3] = acc.w;
          if (lane == 0) { rp[32] = L; rp[33] = M; }
        }
        if (cta == NJOB - 1 && st == 0) *(volatile unsigned*)&g_ticket = 0u;
        named_sync(2, 128);
        {
          const float* rp = red + 64;
          const float MM = fmaxf(fmaxf(rp[33], rp[73]), fmaxf(rp[113], rp[153]));
          const float f0 = ex2(rp[33] - MM), f1 = ex2(rp[73] - MM), f2 = ex2(rp[113] - MM), f3 = ex2(rp[153] - MM);
          const float num = f0 * rp[lane] + f1 * rp[40 + lane] + f2 * rp[80 + lane] + f3 * rp[120 + lane];
          const float den = f0 * rp[32] + f1 * rp[72] + f2 * rp[112] + f3 * rp[152];
          const float ov1 = __fdividef(num, den);
          mbar_wait(BAR(B_WO), 0);
          mbar_wait(BAR(B_WO + 1), 0);
          gemv576<4, false>(sb + OFF_W2, ov1, 0.f, false, sw, g_yp + (size_t)cta * D, tag);
          if (cta >= NEARLY) {
            named_sync(2, 128);
            if (st >= 32 && st < 32 + NREP) st_relaxed32(&g_flag[(st - 32) * 32 + cta - NEARLY], tag);
          }
        }

        if (st == 0) DBG_T(7);
      }
      if (to >= HKV) break;
    }
    if (cta >= NJOB) return;
  }
  uint32_t gbw = 0;
  if (cta < NRED && tid >= 128 && tid < 136) {
    unsigned n = 0;
    gbw = ld_relaxed32(&g_modB[3 * D + cta * 8 + tid - 128]);
    while (!ok2(gbw, tag)) { spin_check(n); gbw = ld_relaxed32(&g_modB[3 * D + cta * 8 + tid - 128]); }
  }
  if (warp >= 4) {
#pragma unroll 1
    for (int i = B_UP; i < B_DOWN + 4; i++) mbar_wait(BAR(i), 0);
  }
  named_sync(1, 256);
  if (tid == 0) DBG_T(9);

  {
    const int g = lane >> 2, t = lane & 3;
    const uint32_t rl = (lane & 7) + ((lane >> 4) << 3), ch = (lane >> 3) & 1;
    const uint32_t wb = sb + OFF_W1 + rl * 80;
    float acc[5][4];
#pragma unroll
    for (int n = 0; n < 5; n++) { acc[n][0] = acc[n][1] = acc[n][2] = acc[n][3] = 0.f; }
    if (tid == 0) DBG_T(20);
    uint32_t r[2][5][4], bv[2][2];
    auto load_k = [&](int buf, int ks) {
      bv[buf][0] = vec32[ks * 8 + t]; bv[buf][1] = vec32[ks * 8 + 4 + t];
#pragma unroll
      for (int n = 0; n < 5; n++) {
        const uint32_t ci = 2 * n + ch;
        const uint32_t off = (ci >= 5) ? W1_BYTES / 2 + (ci - 5) * 16 : ci * 16;
        ldsm4t(wb + ks * 1280 + off, r[buf][n][0], r[buf][n][1], r[buf][n][2], r[buf][n][3]);
      }
    };
    load_k(0, warp);
#pragma unroll
    for (int i = 0; i < 5; i++) {
      const bool more = i < 3 || (i == 3 && warp < 4);
      if (i < 4 && more) load_k((i + 1) & 1, warp + 8 * (i + 1));
      if (i < 4 || warp < 4) {
#pragma unroll
        for (int n = 0; n < 5; n++)
          mma16816(acc[n], r[i & 1][n][0], r[i & 1][n][1], r[i & 1][n][2], r[i & 1][n][3], bv[i & 1][0], bv[i & 1][1]);
      }
    }
    if (tid == 0) DBG_T(21);
    float* part = mbuf;
    if (t < 2) {
#pragma unroll
      for (int n = 0; n < 5; n++) part[warp * 80 + n * 16 + t * 8 + g] = t ? acc[n][2] : acc[n][0];
    }
    named_sync(1, 256);
    if (tid == 0) DBG_T(22);
    float g0 = 0.f, u0 = 0.f, g1 = 0.f, u1 = 0.f;
#pragma unroll
    for (int w = 0; w < 8; w++) {
      g0 += part[w * 80 + lane]; u0 += part[w * 80 + 40 + lane];
      g1 += part[w * 80 + 32 + (lane & 7)]; u1 += part[w * 80 + 72 + (lane & 7)];
    }
    const float alo = bfr(bfr(silu(bfr(g0))) * bfr(u0)), ahi = bfr(bfr(silu(bfr(g1))) * bfr(u1));
    if (tid == 0) DBG_T(10);
    if (tid == 0) DBG_T(24);
    gemv576<8, true>(sb + OFF_RING, alo, ahi, (cta & 1) == 0, warp, g_z + (size_t)cta * D, tag);
  }
  if (tid == 0) DBG_T(11);
  if (cta < NRED) {
    const int j = tid >> 1, hf = tid & 1;
    const float* zp = g_z + (size_t)j * D + cta * 8 + hf * 4;
    backoff(ZD);
    uint4 w = ld_relaxed128(zp);
    unsigned n = 0;
    while (!ok2(w, tag)) { spin_check(n); w = ld_relaxed128(zp); }
    float f0 = __uint_as_float(w.x), f1 = __uint_as_float(w.y), f2 = __uint_as_float(w.z), f3 = __uint_as_float(w.w);
#pragma unroll
    for (int o = 2; o <= 16; o <<= 1) {
      f0 += __shfl_xor_sync(0xffffffffu, f0, o); f1 += __shfl_xor_sync(0xffffffffu, f1, o);
      f2 += __shfl_xor_sync(0xffffffffu, f2, o); f3 += __shfl_xor_sync(0xffffffffu, f3, o);
    }
    float* rp = red + 320;
    if (lane < 2) {
      rp[warp * 8 + lane * 4] = f0; rp[warp * 8 + lane * 4 + 1] = f1;
      rp[warp * 8 + lane * 4 + 2] = f2; rp[warp * 8 + lane * 4 + 3] = f3;
    }
    named_sync(1, 256);
    if (tid >= 128 && tid < 136) {
      const int i = tid - 128;
      float s = 0.f;
#pragma unroll
      for (int w8 = 0; w8 < 8; w8++) s += rp[w8 * 8 + i];
      const int col = cta * 8 + i;
      const float x1 = __bfloat162float(reinterpret_cast<const __nv_bfloat16*>(sp + OFF_QS)[col]);
      p.out[col] = __float2bfloat16_rn(x1 + bfr(bf_hi(gbw) * bfr(s)));
    }
    if (cta == 0 && tid == 0) *(volatile unsigned*)&g_epoch = tag;
  }
  if (tid == 0) DBG_T(12);
}

typedef CUresult (*EncodeFn)(CUtensorMap*, CUtensorMapDataType, cuuint32_t, void*, const cuuint64_t*, const cuuint64_t*,
                             const cuuint32_t*, const cuuint32_t*, CUtensorMapInterleave, CUtensorMapSwizzle,
                             CUtensorMapL2promotion, CUtensorMapFloatOOBfill);

CUtensorMap make_map(EncodeFn enc, const void* base, int rank, const cuuint64_t* dims, const cuuint64_t* strides,
                     const cuuint32_t* box, CUtensorMapSwizzle sw, CUtensorMapL2promotion pr) {
  CUtensorMap m;
  cuuint32_t es[3] = {1, 1, 1};
  enc(&m, CU_TENSOR_MAP_DATA_TYPE_BFLOAT16, rank, const_cast<void*>(base), dims, strides, box, es,
      CU_TENSOR_MAP_INTERLEAVE_NONE, sw, pr, CU_TENSOR_MAP_FLOAT_OOB_FILL_NONE);
  return m;
}

}

extern "C" void kernel_launch(void* const* d_in, const int* in_sizes, int n_in, void* d_out, int out_size) {
  (void)in_sizes; (void)n_in; (void)out_size;
  static EncodeFn enc = nullptr;
  static int nsm = 0;
  if (!enc) {
    void* fn = nullptr;
    cudaDriverEntryPointQueryResult qr;
    cudaGetDriverEntryPoint("cuTensorMapEncodeTiled", &fn, cudaEnableDefault, &qr);
    enc = (EncodeFn)fn;
    int dev = 0;
    cudaGetDevice(&dev);
    cudaDeviceGetAttribute(&nsm, cudaDevAttrMultiProcessorCount, dev);
    cudaFuncSetAttribute(fused_kernel, cudaFuncAttributeMaxDynamicSharedMemorySize, SMEM_BYTES);
  }
  CUtensorMap mK, mV, mModA, mMod, mWq, mG, mU;
  {
    cuuint64_t dims[3] = {64, (cuuint64_t)HKV * SK, 2};
    cuuint64_t str[2] = {256, 128};
    cuuint32_t box[3] = {64, R, 2};
    mK = make_map(enc, d_in[1], 3, dims, str, box, CU_TENSOR_MAP_SWIZZLE_128B, CU_TENSOR_MAP_L2_PROMOTION_L2_256B);
    mV = make_map(enc, d_in[2], 3, dims, str, box, CU_TENSOR_MAP_SWIZZLE_128B, CU_TENSOR_MAP_L2_PROMOTION_L2_256B);
  }
  {
    cuuint64_t dims[2] = {NMOD, D};
    cuuint64_t str[1] = {NMOD * 2};
    cuuint32_t box[2] = {32, 192};
    mMod = make_map(enc, d_in[10], 2, dims, str, box, CU_TENSOR_MAP_SWIZZLE_64B, CU_TENSOR_MAP_L2_PROMOTION_L2_256B);
    cuuint32_t boxa[2] = {16, 192};
    mModA = make_map(enc, d_in[10], 2, dims, str, boxa, CU_TENSOR_MAP_SWIZZLE_NONE, CU_TENSOR_MAP_L2_PROMOTION_L2_256B);
  }
  {
    cuuint64_t dims[2] = {NQ, D};
    cuuint64_t str[1] = {NQ * 2};
    cuuint32_t box[2] = {32, 192};
    mWq = make_map(enc, d_in[3], 2, dims, str, box, CU_TENSOR_MAP_SWIZZLE_64B, CU_TENSOR_MAP_L2_PROMOTION_L2_256B);
  }
  {
    cuuint64_t dims[2] = {FF, D};
    cuuint64_t str[1] = {FF * 2};
    cuuint32_t box[2] = {40, 192};
    mG = make_map(enc, d_in[6], 2, dims, str, box, CU_TENSOR_MAP_SWIZZLE_NONE, CU_TENSOR_MAP_L2_PROMOTION_L2_256B);
    mU = make_map(enc, d_in[7], 2, dims, str, box, CU_TENSOR_MAP_SWIZZLE_NONE, CU_TENSOR_MAP_L2_PROMOTION_L2_256B);
  }
  Params p;
  p.x = (const __nv_bfloat16*)d_in[0];
  p.c = (const __nv_bfloat16*)d_in[9];
  p.wo = (const __nv_bfloat16*)d_in[4];
  p.wdown = (const __nv_bfloat16*)d_in[8];
  p.out = (__nv_bfloat16*)d_out;
  int G = nsm < MAXG ? nsm : MAXG;
  fused_kernel<<<G, 288, SMEM_BYTES, cudaStreamPerThread>>>(mK, mV, mModA, mMod, mWq, mG, mU, p);
}
```
